```python
import torch

def _softmax(x, axis=-1):
    return torch.softmax(x, dim=axis)
def _gelu(x):
    return torch.nn.functional.gelu(x, approximate="tanh")
def _silu(x):
    return torch.nn.functional.silu(x)
def _sigmoid(x):
    return torch.sigmoid(x)
def _layernorm(x, axis=-1, eps=1e-5):
    m = x.mean(dim=axis, keepdim=True)
    v = x.var(dim=axis, keepdim=True, unbiased=False)
    return (x - m) / torch.sqrt(v + eps)
def _scatter_add(tgt, idx, src, axis=0):
    return tgt.clone().index_add_(axis, idx, src)
def _segment_sum(src, seg, n):
    out = torch.zeros((n,) + src.shape[1:], dtype=src.dtype)
    return out.index_add_(0, seg, src)
def _pad(x, pw):
    flat = tuple(v for pair in reversed(pw) for v in pair)
    return torch.nn.functional.pad(x, flat)

kernel_name = 'concat_heads__compressed_kv_cla__mha_block_cached__decode'

def setup_inputs():

    _w = (lambda a: (lambda t: t.to(torch.bfloat16) if t.is_floating_point() else t)(torch.as_tensor(a)))
    def _A_setup():
        B, H, Sq, Sk, D, M = 4, 32, 1, 4096, 128, 512
        Dc = 4 * D
        return {
            "x": _w((lambda *s: torch.randn(*s, dtype=torch.bfloat16) * 3.2)(B, Sq, M)),
            "c_kv": _w((lambda *s: torch.randn(*s, dtype=torch.bfloat16) * 0.1)(B, Sk, Dc)),
            "w_q": _w((lambda *s: torch.randn(*s, dtype=torch.bfloat16) * 6.4)(M, H, D) * (M ** -0.5)),
            "w_uk": _w((lambda *s: torch.randn(*s, dtype=torch.bfloat16) * 6.4)(Dc, H, D) * (Dc ** -0.5)),
            "w_uv": _w((lambda *s: torch.randn(*s, dtype=torch.bfloat16) * 0.1)(Dc, H, D) * (Dc ** -0.5)),
            "w_o": _w((lambda *s: torch.randn(*s, dtype=torch.bfloat16) * 0.1)(H, D, M) * ((H * D) ** -0.5)),
        }
    _A_in = _A_setup()

    def _B_setup():
        B, Sq, D = 4, 1, 512
        H, Sk, Dh = 32, 4096, 128
        return {
            "x": _w((lambda *s: torch.randn(*s, dtype=torch.bfloat16) * 1.6)(B, Sq, D)),
            "k_cache": _w((lambda *s: torch.randn(*s, dtype=torch.bfloat16) * 1.6)(B, H, Sk, Dh)),
            "v_cache": _w((lambda *s: torch.randn(*s, dtype=torch.bfloat16) * 0.05)(B, H, Sk, Dh)),
            "wq": _w((lambda *s: torch.randn(*s, dtype=torch.bfloat16) * 1.6)(D, H * Dh) * (D ** -0.5)),
            "wo": _w((lambda *s: torch.randn(*s, dtype=torch.bfloat16) * 0.05)(H * Dh, D) * ((H * Dh) ** -0.5)),
        }
    _B_in = _B_setup()

    return {
        "A_x": _A_in["x"],
        "A_c_kv": _A_in["c_kv"],
        "A_w_q": _A_in["w_q"],
        "A_w_uk": _A_in["w_uk"],
        "A_w_uv": _A_in["w_uv"],
        "A_w_o": _A_in["w_o"],
        "B_x": _B_in["x"],
        "B_k_cache": _B_in["k_cache"],
        "B_v_cache": _B_in["v_cache"],
        "B_wq": _B_in["wq"],
        "B_wo": _B_in["wo"],
    }

def reference(A_x, A_c_kv, A_w_q, A_w_uk, A_w_uv, A_w_o, B_x, B_k_cache, B_v_cache, B_wq, B_wo):
    def _A_ref(x, c_kv, w_q, w_uk, w_uv, w_o):
        B, Sq, M = x.shape[0], x.shape[1], x.shape[2]
        Sk = c_kv.shape[1]
        H, D = w_q.shape[1], w_q.shape[2]
        q = torch.einsum("bqm,mhd->bhqd", x, w_q)
        k = torch.einsum("bkc,chd->bhkd", c_kv, w_uk)
        v = torch.einsum("bkc,chd->bhkd", c_kv, w_uv)
        scores = torch.einsum("bhqd,bhkd->bhqk", q, k) * (D ** -0.5)
        off = Sk - Sq
        qi = torch.arange(Sq)[:, None]
        kj = torch.arange(Sk)[None, :]
        cmask = kj <= (qi + off)
        scores = torch.where(cmask[None, None], scores, -1e9)
        p = _softmax(scores, axis=-1)
        ctx = torch.einsum("bhqk,bhkd->bhqd", p, v)
        return torch.einsum("bhqd,hdm->bqm", ctx, w_o)

    def _B_ref(x, k_cache, v_cache, wq, wo):
        B, Sq, D = x.shape
        H, Dh = 32, 128
        q = (lambda x, *d: x.permute(*d))((x @ wq).reshape(B, Sq, H, Dh), 0, 2, 1, 3)
        scores = torch.einsum("bhqd,bhkd->bhqk", q, k_cache) * (Dh ** -0.5)
        p = _softmax(scores, axis=-1)
        o = torch.einsum("bhqk,bhkd->bhqd", p, v_cache)
        return (lambda x, *d: x.permute(*d))(o, 0, 2, 1, 3).reshape(B, Sq, H * Dh) @ wo

    a = _A_ref(A_x, A_c_kv, A_w_q, A_w_uk, A_w_uv, A_w_o)
    b = _B_ref(B_x, B_k_cache, B_v_cache, B_wq, B_wo)
    return torch.concatenate([a, b], axis=-1)
```

```cpp
#include <cuda.h>
#include <cuda_runtime.h>
#include <cuda_bf16.h>
#include <stdint.h>

namespace {

#define TV_WSTART 3
#define TV_WMIN 2
#define TV_LEAD 18
#define TV_LEADE 15
#define TV_IEND 110
#define TV_GAIN 1
#define TV_TAU 650
#define TV_QSLEEP 1500
#define TV_ASLEEP 16
#define TV_ASLEEP2 8
#define TV_ITE 12
#define TV_WESTEP 8
#define TV_MERGE 1
#define TV_GSLEEP 2500
#define TV_CTXSLEEP 6
#define TV_MERGE0 6
#define TV_CNT0 56
#define TV_SVC 64
#define TV_GO 1
#define TV_TRIG 541
#define TV_TRIGD 0
#define TV_PSTOP 6
#define TV_X0 80
#define TV_X1 0
enum { T_WSTART, T_WMIN, T_LEAD, T_LEADE, T_IEND, T_GAIN, T_TAU, T_QSLEEP, T_ASLEEP, T_ASLEEP2, T_ITE, T_WESTEP, T_MERGE, T_GSLEEP, T_CTXSLEEP, T_MERGE0, T_CNT0, T_SVC, T_GO, T_TRIG, T_TRIGD, T_PSTOP, T_X0, T_X1, T_COUNT };
#define TUNED(k) (TV_##k)

constexpr int TK = 64;
constexpr int TILE_BYTES = TK * 256;
constexpr int NS = 6;
constexpr int WMAX = 6;
constexpr int NSW = 8;
constexpr int NTHREADS = (4 + NSW) * 32;
constexpr int SPLIT = 4;
constexpr int AKEYS = 4096 / SPLIT;
constexpr int ATILES = AKEYS / 32;
constexpr int ASTAGES = 6;
constexpr int NCTA = 132;
constexpr int APER = 8;
constexpr int NB = NCTA - 4 * SPLIT;
constexpr int R_JOIN = 12, R_LATE = 16;
static_assert(R_JOIN * NB + (R_LATE - R_JOIN) * NCTA == 120 * 16, "early chunks");
constexpr int I_BOX = 8 * (R_LATE + 1);
__device__ __forceinline__ int early_pair(int n) { return n + max(n - 96, 0) / 3; }
__device__ __forceinline__ int late_pair(int vid) { return 99 + 4 * (vid >> 4); }
__device__ __forceinline__ int chunk_of(int r, int wk, int vid) {
    const int c = r * NB + max(r - R_JOIN, 0) * (NCTA - NB) + wk;
    return r == R_LATE ? 16 * late_pair(vid) + (vid & 15) : 16 * early_pair(c >> 4) + (c & 15);
}

#define CGRP 2
constexpr int CHUNK_STEP = CGRP * TILE_BYTES;
__device__ __forceinline__ size_t chunk_off(unsigned c) { return (size_t)(4 * c - 3 * (c % CGRP)) * TILE_BYTES; }

constexpr int OFF_RING = 0;
constexpr int OFF_SIDE = NS * TILE_BYTES;
constexpr int OFF_SCR = OFF_SIDE + 98304;
constexpr int OFF_X = OFF_SCR;
constexpr int XROW = 264;
constexpr int OFF_RED = OFF_SCR + 8192;
constexpr int OFF_ARED = OFF_SCR;
constexpr int OFF_AP = OFF_ARED + 4 * 32 * 40 * 4;
constexpr int OFF_AALPHA = OFF_AP + 2 * 32 * 80;
constexpr int OFF_OPART = OFF_AALPHA + 256;
constexpr int OFF_ML = OFF_OPART + 2 * 512;
constexpr int OFF_DONE = OFF_ML + 16;
constexpr int OFF_WIN = OFF_DONE + 8;
constexpr int OFF_VEC = OFF_WIN + 8;
constexpr int OFF_Q = OFF_VEC + 4 * 68 * 4;
constexpr int OFF_BAR = OFF_Q + (R_LATE + 1) * 256;
enum { SI_WQ = 0, SI_WUK = 4, SI_WE = 6, SI_OPART = 10, SI_WO = 12, SI_COUNT = 16 };
enum {
    MB_X = 0, MB_SIDE = 1, MB_EARLY = MB_SIDE + 4,
    MB_FULL = MB_SIDE + SI_COUNT,
    MB_AFULL = MB_FULL + NS,
    MB_CNT = MB_AFULL + ASTAGES,
    MB_GO,
    MB_EMPTY,
    MB_F0 = MB_EMPTY + NS, MB_FU, MB_F2, MB_F3,
    MB_Q,
    MB_COUNT
};
constexpr int SMEM_BYTES = OFF_BAR + MB_COUNT * 8;
static_assert(SMEM_BYTES <= 232448, "smem");
constexpr int BLK_W = OFF_SIDE;
constexpr int BLK_U = OFF_SIDE + 65536;

constexpr int BAR_B = 9  , BAR_S = 2, BAR_R = 5, BAR_P = 6, BAR_E = 7;

constexpr float SCALE = 0.08838834764831845f;
constexpr float LOG2E = 1.4426950408889634f;
constexpr unsigned SPIN_LIMIT = 1u << 22;

struct Scratch {
    float opart[32 * SPLIT * 2048];
    unsigned qB[4 * 2048];
    unsigned qA[4 * 2048];
    unsigned qabs[4 * 8192];
    unsigned ctx[4 * 2048];
    unsigned oB[4 * 2048];
    unsigned part[2048 * 128];
    unsigned pml[2048 * 2];
    float2 ml[32 * SPLIT * 4];
    unsigned prog, pad[31];
    unsigned cnt;
};
__device__ __align__(128) Scratch g_scratch;

struct Ptrs {
    const __nv_bfloat16 *K, *V, *xA, *xB;
    __nv_bfloat16* out;
    Scratch* sc;
};
struct Maps {
    CUtensorMap tm[7];
};
struct Params : Ptrs {
    const CUtensorMap* tm;
};

#define PROF(i)
#define PROF2(i)

__device__ __forceinline__ uint32_t smem_u32(const void* p) { return (uint32_t)__cvta_generic_to_shared(p); }
__device__ __forceinline__ void mbar_init(uint32_t bar, int cnt) {
    asm volatile("mbarrier.init.shared::cta.b64 [%0], %1;" ::"r"(bar), "r"(cnt) : "memory");
}
__device__ __forceinline__ void mbar_expect_tx(uint32_t bar, uint32_t bytes) {
    asm volatile("mbarrier.arrive.expect_tx.shared::cta.b64 _, [%0], %1;" ::"r"(bar), "r"(bytes) : "memory");
}
__device__ __forceinline__ bool mbar_try(uint32_t bar, uint32_t parity) {
    uint32_t ok;
    asm volatile("{\n .reg .pred p;\n mbarrier.try_wait.parity.shared::cta.b64 p, [%1], %2;\n selp.u32 %0, 1, 0, p;\n}"
                 : "=r"(ok) : "r"(bar), "r"(parity) : "memory");
    return ok;
}
__device__ __forceinline__ void mbar_wait(uint32_t bar, uint32_t parity) {
    unsigned spins = 0;
    while (!mbar_try(bar, parity))
        if (++spins > SPIN_LIMIT) __trap();
}
__device__ __forceinline__ bool mbar_test(uint32_t bar, uint32_t parity) {
    uint32_t ok;
    asm volatile("{\n .reg .pred p;\n mbarrier.test_wait.parity.shared::cta.b64 p, [%1], %2;\n selp.u32 %0, 1, 0, p;\n}"
                 : "=r"(ok) : "r"(bar), "r"(parity) : "memory");
    return ok;
}
__device__ __forceinline__ void warp_release(uint32_t bar, int lane, float dep) {
    const uint32_t any = __ballot_sync(0xffffffffu, dep != dep);
    if (lane == 0)
        asm volatile("{\n .reg .pred q;\n setp.eq.u32 q, %1, 0;\n @q mbarrier.arrive.shared::cta.b64 _, [%0];\n"
                     " @!q mbarrier.arrive.shared::cta.b64 _, [%0];\n}" ::"r"(bar), "r"(any) : "memory");
}
__device__ __forceinline__ bool elect_one() {
    uint32_t e;
    asm volatile("{\n .reg .pred p;\n elect.sync _|p, 0xffffffff;\n selp.u32 %0, 1, 0, p;\n}" : "=r"(e));
    return e;
}
__device__ __forceinline__ int lds_volatile(uint32_t addr) {
    int v;
    asm volatile("ld.volatile.shared.u32 %0, [%1];" : "=r"(v) : "r"(addr) : "memory");
    return v;
}
__device__ __forceinline__ int2 lds_volatile2(uint32_t addr) {
    int2 v;
    asm volatile("ld.volatile.shared.v2.u32 {%0, %1}, [%2];" : "=r"(v.x), "=r"(v.y) : "r"(addr) : "memory");
    return v;
}
__device__ __forceinline__ void sts_volatile2(uint32_t addr, int a, int b) {
    asm volatile("st.volatile.shared.v2.u32 [%0], {%1, %2};" ::"r"(addr), "r"(a), "r"(b) : "memory");
}
__device__ __forceinline__ void sts_volatile(uint32_t addr, int v) {
    asm volatile("st.volatile.shared.u32 [%0], %1;" ::"r"(addr), "r"(v) : "memory");
}
__device__ __forceinline__ unsigned now_ns() {
    unsigned t;
    asm volatile("mov.u32 %0, %%globaltimer_lo;" : "=r"(t) :: "memory");
    return t;
}
__device__ __forceinline__ int clock_after(unsigned dep) {
    int c;
    asm volatile("{\n .reg .pred q;\n setp.eq.u32 q, %1, 0;\n @q mov.u32 %0, %%globaltimer_lo;\n @!q mov.u32 %0, %%globaltimer_lo;\n}" : "=r"(c) : "r"(dep) : "memory");
    return c;
}
__device__ __forceinline__ void fence_mbar_init() { asm volatile("fence.mbarrier_init.release.cluster;" ::: "memory"); }
__device__ __forceinline__ uint64_t policy_evict_first() {
    uint64_t pol;
    asm volatile("createpolicy.fractional.L2::evict_first.b64 %0, 1.0;" : "=l"(pol));
    return pol;
}
__device__ __forceinline__ uint64_t policy_evict_normal() {
    uint64_t pol;
    asm volatile("createpolicy.fractional.L2::evict_normal.b64 %0, 1.0;" : "=l"(pol));
    return pol;
}
__device__ __forceinline__ void bulk_load(uint32_t dst, const void* src, uint32_t bytes, uint32_t bar, uint64_t pol) {
    asm volatile("cp.async.bulk.shared::cluster.global.mbarrier::complete_tx::bytes.L2::cache_hint [%0], [%1], %2, [%3], %4;"
                 ::"r"(dst), "l"(src), "r"(bytes), "r"(bar), "l"(pol) : "memory");
}
__device__ __forceinline__ void bulk_load_nohint(uint32_t dst, const void* src, uint32_t bytes, uint32_t bar) {
    asm volatile("cp.async.bulk.shared::cluster.global.mbarrier::complete_tx::bytes [%0], [%1], %2, [%3];"
                 ::"r"(dst), "l"(src), "r"(bytes), "r"(bar) : "memory");
}
__device__ __forceinline__ void tma2d_hint(uint32_t dst, const CUtensorMap* tm, int x, int y, uint32_t bar, uint64_t pol) {
    asm volatile("cp.async.bulk.tensor.2d.shared::cluster.global.mbarrier::complete_tx::bytes.L2::cache_hint [%0], [%1, {%3, %4}], [%2], %5;"
                 ::"r"(dst), "l"(tm), "r"(bar), "r"(x), "r"(y), "l"(pol) : "memory");
}
__device__ __forceinline__ void ldsm4(uint32_t& r0, uint32_t& r1, uint32_t& r2, uint32_t& r3, uint32_t addr) {
    asm volatile("ldmatrix.sync.aligned.m8n8.x4.shared.b16 {%0,%1,%2,%3}, [%4];"
                 : "=r"(r0), "=r"(r1), "=r"(r2), "=r"(r3) : "r"(addr) : "memory");
}
__device__ __forceinline__ void ldsm4t(uint32_t& r0, uint32_t& r1, uint32_t& r2, uint32_t& r3, uint32_t addr) {
    asm volatile("ldmatrix.sync.aligned.m8n8.x4.trans.shared.b16 {%0,%1,%2,%3}, [%4];"
                 : "=r"(r0), "=r"(r1), "=r"(r2), "=r"(r3) : "r"(addr) : "memory");
}
__device__ __forceinline__ void mma(float (&c)[4], uint32_t a0, uint32_t a1, uint32_t a2, uint32_t a3, uint32_t b0, uint32_t b1) {
    asm volatile("mma.sync.aligned.m16n8k16.row.col.f32.bf16.bf16.f32 {%0,%1,%2,%3}, {%4,%5,%6,%7}, {%8,%9}, {%0,%1,%2,%3};"
                 : "+f"(c[0]), "+f"(c[1]), "+f"(c[2]), "+f"(c[3])
                 : "r"(a0), "r"(a1), "r"(a2), "r"(a3), "r"(b0), "r"(b1));
}
__device__ __forceinline__ void zero4(float (&c)[4]) { c[0] = c[1] = c[2] = c[3] = 0.f; }
__device__ __forceinline__ void bar_sync(int id, int n) { asm volatile("bar.sync %0, %1;" ::"r"(id), "r"(n) : "memory"); }
__device__ __forceinline__ void bar_arrive(int id, int n) { asm volatile("bar.arrive %0, %1;" ::"r"(id), "r"(n) : "memory"); }
__device__ __forceinline__ float ex2(float x) { float y; asm("ex2.approx.ftz.f32 %0, %1;" : "=f"(y) : "f"(x)); return y; }
__device__ __forceinline__ uint32_t pack_bf16(float lo, float hi) {
    uint32_t r; asm("cvt.rn.bf16x2.f32 %0, %1, %2;" : "=r"(r) : "f"(hi), "f"(lo)); return r;
}
__device__ __forceinline__ float bf_lo(uint32_t u) { return __uint_as_float(u << 16); }
__device__ __forceinline__ float bf_hi(uint32_t u) { return __uint_as_float(u & 0xffff0000u); }
__device__ __forceinline__ uint32_t score_round2(float a, float b) {
    const uint32_t u = pack_bf16(a, b);
    return pack_bf16(bf_lo(u) * SCALE, bf_hi(u) * SCALE);
}
__device__ __forceinline__ float warp_max(float v) {
#pragma unroll
    for (int o = 16; o > 0; o >>= 1) v = fmaxf(v, __shfl_xor_sync(0xffffffffu, v, o));
    return v;
}
__device__ __forceinline__ float redux_max(float v) {
    const int i = __float_as_int(v), m = __reduce_max_sync(0xffffffffu, i ^ ((i >> 31) & 0x7fffffff));
    return __int_as_float(m ^ ((m >> 31) & 0x7fffffff));
}
__device__ __forceinline__ float warp_sum(float v) {
#pragma unroll
    for (int o = 16; o > 0; o >>= 1) v += __shfl_xor_sync(0xffffffffu, v, o);
    return v;
}

__device__ __forceinline__ void ll_store(unsigned* p, unsigned bits) {
    unsigned u = ~bits;
    u = u ? u : 0x80008000u;
    asm volatile("st.relaxed.gpu.global.u32 [%0], %1;" ::"l"(p), "r"(u) : "memory");
}
__device__ __forceinline__ void ll_store2(unsigned* p, unsigned a, unsigned b) {
    unsigned u = ~a, v = ~b;
    u = u ? u : 0x80008000u;
    v = v ? v : 0x80008000u;
    asm volatile("st.relaxed.gpu.global.v2.u32 [%0], {%1, %2};" ::"l"(p), "r"(u), "r"(v) : "memory");
}
__device__ __forceinline__ void ll_store4(unsigned* p, float a, float b, float c, float d) {
    unsigned u[4] = {~__float_as_uint(a), ~__float_as_uint(b), ~__float_as_uint(c), ~__float_as_uint(d)};
#pragma unroll
    for (int k = 0; k < 4; k++) u[k] = u[k] ? u[k] : 0x80008000u;
    asm volatile("st.relaxed.gpu.global.v4.u32 [%0], {%1, %2, %3, %4};" ::"l"(p), "r"(u[0]), "r"(u[1]), "r"(u[2]), "r"(u[3]) : "memory");
}
__device__ __forceinline__ unsigned ll_load(const unsigned* p) {
    unsigned u;
    asm volatile("ld.relaxed.gpu.global.u32 %0, [%1];" : "=r"(u) : "l"(p) : "memory");
    return u;
}
__device__ __forceinline__ uint2 ll_load2(const unsigned* p) {
    uint2 v;
    asm volatile("ld.relaxed.gpu.global.v2.u32 {%0,%1}, [%2];" : "=r"(v.x), "=r"(v.y) : "l"(p) : "memory");
    return v;
}
__device__ __forceinline__ uint4 ll_load4(const unsigned* p) {
    uint4 v;
    asm volatile("ld.relaxed.gpu.global.v4.u32 {%0,%1,%2,%3}, [%4];" : "=r"(v.x), "=r"(v.y), "=r"(v.z), "=r"(v.w) : "l"(p) : "memory");
    return v;
}
__device__ __forceinline__ bool ll_ok4(const uint4& v) { return min(min(v.x, v.y), min(v.z, v.w)) != 0u; }
template <int N>
__device__ __forceinline__ void ll_poll4(uint4 (&v)[N], const unsigned* p, int stride, unsigned sleep_ns = 0) {
    unsigned spins = 0;
    while (true) {
        bool ok = true;
#pragma unroll
        for (int k = 0; k < N; k++) v[k] = ll_load4(p + k * stride);
#pragma unroll
        for (int k = 0; k < N; k++) ok = ok && ll_ok4(v[k]);
        if (ok) break;
        if (sleep_ns) __nanosleep(sleep_ns);
        if (++spins > SPIN_LIMIT) __trap();
    }
    __syncwarp();
#pragma unroll
    for (int k = 0; k < N; k++) v[k] = make_uint4(~v[k].x, ~v[k].y, ~v[k].z, ~v[k].w);
}

__device__ __forceinline__ void bump_counter(unsigned* c) {
    asm volatile("red.relaxed.gpu.global.inc.u32 [%0], %1;" ::"l"(c), "r"(4 * SPLIT + 128 - 1) : "memory");
}
__device__ __forceinline__ void signal_counter(unsigned* c) {
    asm volatile("fence.acq_rel.gpu;" ::: "memory");
    bump_counter(c);
}
__device__ __forceinline__ unsigned ld_acquire(const unsigned* c) {
    unsigned v;
    asm volatile("ld.acquire.gpu.global.u32 %0, [%1];" : "=r"(v) : "l"(c) : "memory");
    return v;
}
__device__ __forceinline__ uint32_t pv_mask(int c, int g, int t) {
    return (c == (g ^ (2 * t)) ? 0x0000ffffu : 0u) | (c == (g ^ (2 * t + 1)) ? 0xffff0000u : 0u);
}

struct Producer {
    uint32_t sbase;
    uint32_t wbar, wpar;
    bool pend;
    int lane;
    uint64_t pol;
    uint32_t si_dst, si_gate;
    int si_x, si_y, si_min;
    bool si_box;
    const void* si_src;
    uint64_t si_pol;
    __device__ __forceinline__ uint32_t mb(int i) const { return sbase + OFF_BAR + i * 8; }
    __device__ __forceinline__ void setup_side(const Params& p, int vid) {
        const int odd = vid & 1, cbk = vid >> 1, u = lane & 1;
        si_box = true; si_min = 0; si_gate = mb(MB_X);
        si_pol = (lane >> 1) == SI_OPART / 2 ? policy_evict_normal() : pol;
        int blk = BLK_U + u * 16384;
        if (lane >= SI_WO) {
            const int q = lane - SI_WO;
            si_src = &p.tm[2 + odd]; blk = BLK_W + q * 16384;
            si_x = 64 * (cbk & 7); si_y = 128 * q + 512 * (cbk >> 3);
        } else if (lane >= SI_OPART) {
            si_box = false; si_src = p.sc->opart + ((cbk >> 1) * SPLIT + 2 * u) * 2048;
            si_gate = mb(MB_CNT);
        } else if (lane >= SI_WE) {
            const int q = lane - SI_WE;
            si_src = &p.tm[5]; blk = BLK_W + q * 16384;
            si_x = 64 * cbk; si_y = 128 * q;
            si_gate = mb(MB_F0); si_min = TUNED(ITE) + TUNED(WESTEP) * q;
        } else {
            si_src = &p.tm[4]; si_x = (vid & 31) * 128 + 64 * u; si_y = 128 * (vid >> 5);
        }
        si_dst = sbase + blk;
    }
    __device__ __forceinline__ bool due(const Params& p, int i, int2 st) const {
        return st.x < TUNED(WSTART) && (int)(now_ns() - (unsigned)st.y) >= (4 * i - (i >= TUNED(IEND) ? TUNED(LEADE) : TUNED(LEAD))) * TUNED(TAU) / 4;
    }
    __device__ __forceinline__ void window(const Params& p, int i, uint32_t bar, uint32_t parity) {
        unsigned busy;
        for (unsigned spins = 0;; spins++) {
            const int2 st = lds_volatile2(sbase + OFF_WIN);
            if (pend) pend = !mbar_test(wbar, wpar);
            busy = __ballot_sync(0xffffffffu, pend);
            const int n = __popc(busy);
            if (__any_sync(0xffffffffu, n < st.x || (n < WMAX && due(p, i, st)))) break;
            if (spins > 16 * SPIN_LIMIT) __trap();
        }
        if (lane == __ffs(~busy) - 1) { wbar = bar; wpar = parity; pend = true; }
    }
    __device__ __forceinline__ void side(const Params& p, int id, int i) {
        const uint32_t bar = mb(MB_SIDE + id);
        if ((id >> 1) != SI_OPART / 2) window(p, i, bar, 0);
        if (lane == id) {
            mbar_expect_tx(bar, TILE_BYTES);
            if (si_box) {
                tma2d_hint(si_dst, (const CUtensorMap*)si_src, si_x, si_y, bar, si_pol);
            } else {
                asm volatile("fence.proxy.async.global;" ::: "memory");
                bulk_load(si_dst, si_src, TILE_BYTES, bar, si_pol);
            }
        }
        __syncwarp();
    }
    __device__ __forceinline__ void a_tile(const Params& p, int row0, int n) {
        const int st = n % ASTAGES;
        if (lane == 0) mbar_expect_tx(mb(MB_AFULL + st), 32768);
        __syncwarp();
        if (lane < 8) tma2d_hint(sbase + st * 32768 + lane * 4096, &p.tm[6], lane * 64, row0 + n * (32 * SPLIT), mb(MB_AFULL + st), pol);
        __syncwarp();
    }
};

__device__ __forceinline__ void first_load(const Params& p, uint32_t sbase, unsigned blk) {
    const uint32_t bar = sbase + OFF_BAR + MB_FULL * 8;
    mbar_init(bar, 1);
    if (blk % APER != APER - 1) {
        const unsigned c = blk - blk / APER;
        fence_mbar_init();
        mbar_expect_tx(bar, TILE_BYTES);
        bulk_load(sbase + OFF_RING, (const char*)p.K + chunk_off(c), TILE_BYTES, bar, policy_evict_first());
    }
}
__device__ __forceinline__ void next_loads(const Params& p, uint32_t sbase, int vid) {
    const uint32_t bars = sbase + OFF_BAR;
    const uint64_t pol = policy_evict_first();
#pragma unroll
    for (int i = 0; i < MB_EARLY; i++) mbar_init(bars + i * 8, 1);
    fence_mbar_init();
    if (vid >= 0) {
#pragma unroll
        for (int q = 0; q < 4; q++) {
            mbar_expect_tx(bars + (MB_SIDE + q) * 8, TILE_BYTES);
            tma2d_hint(sbase + BLK_W + q * 16384, &p.tm[vid & 1], 64 * (vid >> 1), 128 * q, bars + (MB_SIDE + q) * 8, pol);
            if (q == 0) {
                mbar_expect_tx(bars + MB_X * 8, 4096);
                bulk_load_nohint(sbase + OFF_X, (vid & 1) ? p.xA : p.xB, 4096, bars + MB_X * 8);
            }
        }
    }
}

__device__ __forceinline__ void produce(const Params& p, char* smem, int lane, bool isA, int wk, int vid, int row0) {
    Producer pr;
    pr.sbase = smem_u32(smem);
    pr.lane = lane;
    pr.pol = policy_evict_first();
    pr.pend = !isA && lane < 5;
    pr.wbar = pr.mb(lane == 0 ? MB_FULL : MB_SIDE + lane - 1);
    pr.wpar = 0;
    pr.setup_side(p, vid);
    const int i0 = isA ? 8 * R_JOIN : 0;
    int i = isA ? i0 : 1, i_end = isA ? i0 : I_BOX, s = i - i0, ph = 0;
    int chunk = chunk_of(i >> 3, wk, vid);
    const char* src = (const char*)p.K + chunk_off(chunk) + (i & 3) * CHUNK_STEP;
    int nx = SI_WUK, nx_end = vid < 0 ? 0 : isA || (vid & 1) ? SI_WE : SI_WO;
    uint32_t gate = pr.mb(MB_X);
    int gmin = 0;
    bool last_tile = false;
#pragma unroll 1
    for (int phase = 0; phase < 3; phase++) {
#pragma unroll 1
        while (i < i_end || nx < nx_end) {
            if (nx < nx_end && i >= gmin) {
                bool side = true;
                if (i == i_end) mbar_wait(gate, 0);
                else side = __all_sync(0xffffffffu, mbar_test(gate, 0) &&
                                       (last_tile || (i - i0 >= NS && !mbar_test(pr.mb(MB_EMPTY + s), ph ^ 1))));
                if (side) {
                    last_tile = false;
                    pr.side(p, nx, 0);
                    PROF2(160 + nx);
                    nx++;
                    gate = __shfl_sync(0xffffffffu, pr.si_gate, nx);
                    gmin = __shfl_sync(0xffffffffu, pr.si_min, nx);
                    continue;
                }
            }
            last_tile = true;
            const uint32_t full = pr.mb(MB_FULL + s);
            mbar_wait(pr.mb(MB_EMPTY + s), ph ^ 1);
            if (elect_one()) mbar_expect_tx(full, TILE_BYTES);
            pr.window(p, i, full, ph);
            if (elect_one()) bulk_load(pr.sbase + OFF_RING + s * TILE_BYTES, src, TILE_BYTES, full, pr.pol);
            PROF2(i);
            src += CHUNK_STEP;
            if ((++i & 3) == 0) {
                if ((i & 4) == 0) chunk = chunk_of(i >> 3, wk, vid);
                src = (const char*)((i & 4) ? p.V : p.K) + chunk_off(chunk);
            }
            if (++s == NS) { s = 0; ph ^= 1; }
        }
        if (!isA || phase == 2) break;
        if (phase == 0) {
#pragma unroll 1
            for (int k = -ASTAGES; k < ATILES; k++) {
                if (k == 3 - ASTAGES && vid >= 0) mbar_wait(pr.mb(MB_FU), 0);
                if (k >= 0) bar_sync(BAR_R, 352);
                const int n = k < 0 ? k + ASTAGES : k - 2 + ASTAGES;
                if ((k < 0 || k >= 2) && n < ATILES) { pr.a_tile(p, row0, n); PROF2(32 + n); }
            }
            mbar_wait(pr.mb(MB_F3), 0);
            if (vid >= 0 && !(vid & 1)) nx_end = SI_WO;
        } else {
            for (int k = 0; k < 500 && !__any_sync(0xffffffffu, pr.due(p, i0, lds_volatile2(pr.sbase + OFF_WIN))); k++) __nanosleep(100);
            i_end = vid >= 0 ? I_BOX : 8 * R_LATE;
        }
    }
    if (vid < 0) return;
    mbar_wait(pr.mb((vid & 1) ? MB_F0 : MB_F2), 0);
#pragma unroll 1
    for (int u = 0; u < 4; u++) {
        pr.side(p, SI_WO + u, I_BOX + u);
        if (u == TUNED(GO) && elect_one()) mbar_expect_tx(pr.mb(MB_GO), 0);
        PROF2(I_BOX + u);
    }
}

__device__ __forceinline__ void consume(const Params& p, char* smem, bool isA, int wk, int vid, int w, int lane) {
    const uint32_t sbase = smem_u32(smem);
    const uint32_t bars = sbase + OFF_BAR;
    const int g = lane >> 2, t = lane & 3;
    const int mat = lane >> 3, r8 = lane & 7;
    const uint32_t kbase = sbase + OFF_RING + (r8 + 8 * (mat & 1)) * 256 + (mat >> 1) * 128 + r8 * 16;
    const uint32_t vbase = sbase + OFF_RING + (r8 + 8 * (mat >> 1)) * 256 + (mat & 1) * 128 + r8 * 16;
    uint32_t mask[8];
#pragma unroll
    for (int c = 0; c < 8; c++) mask[c] = pv_mask(c, g, t);
    uint32_t* qtab = (uint32_t*)(smem + OFF_Q);
    if (!isA) {
        mbar_wait(bars + MB_F0 * 8, 0);
        __nanosleep(TUNED(QSLEEP));
        const unsigned* src = p.sc->qB + (chunk_of(0, wk, vid) >> 4) * 64 + lane;
        unsigned q0, q1, spins = 0;
        while (true) {
            q0 = ll_load(src);
            q1 = ll_load(src + 32);
            if (q0 && q1) break;
            __nanosleep(200);
            if (++spins > SPIN_LIMIT) __trap();
        }
        qtab[lane] = ~q0;
        qtab[32 + lane] = ~q1;
        __syncwarp();
        if (w == 0) PROF(1);
    }
    const int r_end = vid >= 0 ? R_LATE + 1 : R_LATE;
    int s = w, ph = 0;
    int done = 0;
#pragma unroll 1
    for (int r = isA ? R_JOIN : 0; r < r_end; r++) {
        const int chunk = chunk_of(r, wk, vid);
        if (r >= 1) mbar_wait(bars + MB_Q * 8, 0);
        uint32_t qf[8][2];
#pragma unroll
        for (int c = 0; c < 8; c++) {
            qf[c][0] = qtab[r * 64 + (c ^ g) * 4 + t];
            qf[c][1] = qtab[r * 64 + 32 + (c ^ g) * 4 + t];
        }
        uint32_t pf[2][4][2];
        float m[2], l[2];
#pragma unroll
        for (int u = 0; u < 2; u++) {
            mbar_wait(bars + (MB_FULL + s) * 8, ph);
            done++;
            float acc[4][4];
#pragma unroll
            for (int gr = 0; gr < 4; gr++) zero4(acc[gr]);
#pragma unroll
            for (int c = 0; c < 8; c++) {
#pragma unroll
                for (int gr = 0; gr < 4; gr++) {
                    uint32_t a0, a1, a2, a3;
                    ldsm4(a0, a1, a2, a3, (kbase ^ (c << 4)) + s * TILE_BYTES + gr * 4096);
                    mma(acc[gr], a0, a1, a2, a3, qf[c][0], qf[c][1]);
                }
            }
            warp_release(bars + (MB_EMPTY + s) * 8, lane, (acc[0][0] + acc[1][0]) + (acc[2][0] + acc[3][0]));
#pragma unroll
            for (int gr = 0; gr < 4; gr++) {
                const uint32_t su = score_round2((g & 1) ? acc[gr][1] : acc[gr][0], (g & 1) ? acc[gr][3] : acc[gr][2]);
                const uint32_t x = __shfl_sync(0xffffffffu, su, 9 * t), y = __shfl_sync(0xffffffffu, su, 9 * t + 4);
                pf[u][gr][0] = __byte_perm(x, y, 0x5410);
                pf[u][gr][1] = __byte_perm(x, y, 0x7632);
            }
            m[u] = -INFINITY;
            l[u] = 0.f;
#pragma unroll
            for (int k = 0; k < 8; k++) m[u] = fmaxf(m[u], fmaxf(bf_lo(pf[u][k >> 1][k & 1]), bf_hi(pf[u][k >> 1][k & 1])));
            m[u] = fmaxf(m[u], __shfl_xor_sync(0xffffffffu, m[u], 1));
            m[u] = fmaxf(m[u], __shfl_xor_sync(0xffffffffu, m[u], 2));
#pragma unroll
            for (int k = 0; k < 8; k++) {
                uint32_t& x = pf[u][k >> 1][k & 1];
                const float e0 = ex2((bf_lo(x) - m[u]) * LOG2E), e1 = ex2((bf_hi(x) - m[u]) * LOG2E);
                l[u] += e0 + e1;
                x = pack_bf16(e0, e1);
            }
            l[u] += __shfl_xor_sync(0xffffffffu, l[u], 1);
            l[u] += __shfl_xor_sync(0xffffffffu, l[u], 2);
            if (lane == 0) sts_volatile(sbase + OFF_DONE + 4 * w, done);
            if ((s += 2) >= NS) { s -= NS; ph ^= 1; }
        }
        const float mw = fmaxf(m[0], m[1]);
        float o[4] = {0.f, 0.f, 0.f, 0.f}, lw = 0.f;
#pragma unroll
        for (int u = 0; u < 2; u++) {
            const float a = ex2((m[u] - mw) * LOG2E);
            lw = fmaf(a, l[u], lw);
            float oacc[4][4];
#pragma unroll
            for (int gr = 0; gr < 4; gr++) zero4(oacc[gr]);
            mbar_wait(bars + (MB_FULL + s) * 8, ph);
            if (u) PROF(2 + w);
            done++;
#pragma unroll
            for (int c = 0; c < 8; c++) {
#pragma unroll
                for (int gr = 0; gr < 4; gr++) {
                    uint32_t a0, a1, a2, a3;
                    ldsm4t(a0, a1, a2, a3, (vbase ^ (c << 4)) + s * TILE_BYTES + gr * 4096);
                    mma(oacc[gr], a0, a1, a2, a3, pf[u][gr][0] & mask[c], pf[u][gr][1] & mask[c]);
                }
            }
#pragma unroll
            for (int e = 0; e < 4; e++) o[e] = fmaf(a, (oacc[0][e] + oacc[1][e]) + (oacc[2][e] + oacc[3][e]), o[e]);
            warp_release(bars + (MB_EMPTY + s) * 8, lane, o[0]);
            if (lane == 0) sts_volatile(sbase + OFF_DONE + 4 * w, done);
            if ((s += 2) >= NS) { s -= NS; ph ^= 1; }
        }
        float4* op = (float4*)(smem + OFF_OPART) + (r & 1) * 32 + lane;
        float2* ml = (float2*)(smem + OFF_ML) + (r & 1);
        if (w == 0) {
            *op = make_float4(o[0], o[1], o[2], o[3]);
            if (lane == 0) *ml = make_float2(mw, lw);
            bar_arrive(BAR_B + (r & 1), 64);
        } else {
            bar_sync(BAR_B + (r & 1), 64);
            const float2 ot = *ml;
            const float4 oo = *op;
            const float M = fmaxf(mw, ot.x), a = ex2((mw - M) * LOG2E), b = ex2((ot.x - M) * LOG2E);
            ll_store4(p.sc->part + chunk * 128 + lane * 4, a * o[0] + b * oo.x, a * o[1] + b * oo.y,
                      a * o[2] + b * oo.z, a * o[3] + b * oo.w);
            if (lane == 0) ll_store2(p.sc->pml + chunk * 2, __float_as_uint(M), __float_as_uint(a * lw + b * ot.y));
            PROF(10);
        }
    }
}

__device__ __forceinline__ uint2 merge_chunks(const Params& p, int pair, int lane) {
    Scratch* sc = p.sc;
    const unsigned* pm = sc->pml + pair * 32 + 2 * (lane & 15);
    const unsigned* base = sc->part + pair * 2048 + 4 * lane;
    unsigned um = 0, ul = 0;
    uint4 u[16];
#pragma unroll
    for (int c = 0; c < 16; c++) u[c] = make_uint4(0, 0, 0, 0);
    for (unsigned spins = 0;; spins++) {
        if (!(um && ul)) { um = ll_load(pm); ul = ll_load(pm + 1); }
#pragma unroll
        for (int c = 0; c < 16; c++)
            if (!ll_ok4(u[c])) u[c] = ll_load4(base + c * 128);
        bool ok = um && ul;
#pragma unroll
        for (int c = 0; c < 16; c++) ok &= ll_ok4(u[c]);
        if (__all_sync(0xffffffffu, ok)) break;
        __nanosleep(100);
        if (spins > SPIN_LIMIT) __trap();
    }
    const float m = __uint_as_float(~um);
    const float M = redux_max(m);
    const float wgt = ex2((m - M) * LOG2E);
    float l = wgt * __uint_as_float(~ul);
#pragma unroll
    for (int k = 8; k > 0; k >>= 1) l += __shfl_xor_sync(0xffffffffu, l, k);
    float o[4] = {0.f, 0.f, 0.f, 0.f};
#pragma unroll
    for (int c = 0; c < 16; c++) {
        const float wc = __shfl_sync(0xffffffffu, wgt, c);
        o[0] = fmaf(wc, __uint_as_float(~u[c].x), o[0]); o[1] = fmaf(wc, __uint_as_float(~u[c].y), o[1]);
        o[2] = fmaf(wc, __uint_as_float(~u[c].z), o[2]); o[3] = fmaf(wc, __uint_as_float(~u[c].w), o[3]);
    }
    const float inv = __frcp_rn(l);
    const uint32_t lo = pack_bf16(o[0] * inv, o[2] * inv), hi = pack_bf16(o[1] * inv, o[3] * inv);
    const bool odd = lane & 4;
    const uint32_t x = __shfl_xor_sync(0xffffffffu, odd ? lo : hi, 4), a = odd ? x : lo, b = odd ? hi : x;
    return make_uint2(__byte_perm(a, b, 0x5410), __byte_perm(a, b, 0x7632));
}

__device__ __forceinline__ int qabs_word(int b, int h, int j, int ks, int nt, int t) {
    return b * 8192 + (((h >> 4) + 2 * j) * 8 + ks) * 128 + ((h & 7) * 4 + t) * 4 + ((h >> 3) & 1) + 2 * nt;
}
__device__ __forceinline__ void service(const Params& p, char* smem, bool isA, int vid, int lane) {
    const int paced = I_BOX - TUNED(PSTOP);
    const uint32_t sbase = smem_u32(smem);
    const int i0 = isA ? 8 * R_JOIN : 0, stop = vid >= 0 ? paced : 8 * R_LATE - 4;
    const int c = 16 * vid + 15;
    const int rl = c < R_JOIN * NB ? c / NB : R_JOIN + (c - R_JOIN * NB) / NCTA;
    const int due = 8 * (rl + 1) + (rl + 1 == R_LATE ? TUNED(MERGE) : TUNED(MERGE0));
    const int ow = 8 * (lane & 3) + (lane & 4) + (lane >> 3);
    bool merged = vid < 0 || vid >= 120, counted = vid < 0;
    int last = i0, z = 0;
    unsigned t0 = clock(), t1 = t0, prev = 0;
    if (isA) mbar_wait(sbase + OFF_BAR + MB_F3 * 8, 0);
    for (unsigned spins = 0; last < stop || !counted || !merged; spins++) {
        const int pos = __shfl_sync(0xffffffffu, i0 + lds_volatile(sbase + OFF_DONE) + lds_volatile(sbase + OFF_DONE + 4), 0);
        if (!merged && pos > due) {
            const int pair = early_pair(vid);
            const uint2 o = merge_chunks(p, pair, lane);
            ll_store(p.sc->oB + pair * 64 + ow, o.x);
            ll_store(p.sc->oB + pair * 64 + ow + 32, o.y);
#pragma unroll
            for (int k = 0; k < 16; k++) *(uint4*)(p.sc->part + pair * 2048 + k * 128 + 4 * lane) = make_uint4(0, 0, 0, 0);
            p.sc->pml[pair * 32 + lane] = 0;
            *(uint2*)(p.sc->qB + pair * 64 + 2 * lane) = make_uint2(0, 0);
            PROF(12);
            merged = true;
            continue;
        }
        const int cur = min(pos, stop);
        const unsigned now = __shfl_sync(0xffffffffu, (unsigned)clock(), 0);
        const bool look = isA ? now - t1 > 1200 : cur > last;
        unsigned old = 0;
        if (look && lane == 0)
            asm volatile("atom.relaxed.gpu.global.add.u32 %0, [%1], %2;" : "=r"(old) : "l"(&p.sc->prog), "r"(isA ? 0 : cur - last) : "memory");
        if (!counted && now - t0 > 2000 && (isA || pos > TUNED(CNT0))) {
            t0 = now;
            if (__all_sync(0xffffffffu, ld_acquire(&p.sc->cnt) >= 4 * SPLIT)) {
                if (lane == 0) {
                    mbar_expect_tx(sbase + OFF_BAR + MB_CNT * 8, 0);
                    bump_counter(&p.sc->cnt);
                }
                *(uint2*)(p.sc->qA + vid * 64 + lane * 2) = make_uint2(0, 0);
                *(uint4*)(p.sc->qabs + vid * 256 + lane * 4) = make_uint4(0, 0, 0, 0);
                *(uint4*)(p.sc->qabs + vid * 256 + 128 + lane * 4) = make_uint4(0, 0, 0, 0);
                counted = true;
            }
        }
        if (look) {
            if (lane == 0) {
                if (!isA && old + (cur - last) == paced * NB) p.sc->prog = 0;
                if (old > prev && old >= 6 * NB && old < (paced - 2) * NB) {
                    const int zn = clock_after(old) - old * TUNED(TAU) / NB + ((vid >> 4) & 7) * TUNED(X0);
                    z = prev ? z + ((zn - z) >> TUNED(GAIN)) : zn;
                    prev = old;
                    sts_volatile2(sbase + OFF_WIN, TUNED(WMIN), z);
                }
            }
            t1 = now;
        } else {
            __nanosleep(TUNED(SVC));
        }
        last = cur;
        if (spins > SPIN_LIMIT) __trap();
    }
}

__device__ __forceinline__ void softmax_A(const Params& p, char* smem, int w, int lane, int ab, int asp) {
    const int mat = lane >> 3, r = lane & 7;
    float m_run[4], l_run[4];
#pragma unroll
    for (int i = 0; i < 4; i++) { m_run[i] = -INFINITY; l_run[i] = 0.f; }
    const float* red = (const float*)(smem + OFF_ARED);
    for (int k = 0; k < ATILES; k++) {
        bar_sync(BAR_R, 352);
        float4 s[4];
        float mt[4];
#pragma unroll
        for (int i = 0; i < 4; i++) {
            const float* src = red + (16 * w + 4 * i + mat) * 40 + 4 * r;
            const float4 a = *(const float4*)src, b = *(const float4*)(src + 32 * 40);
            const float4 c = *(const float4*)(src + 64 * 40), d = *(const float4*)(src + 96 * 40);
            const uint32_t v0 = score_round2((a.x + b.x) + (c.x + d.x), (a.y + b.y) + (c.y + d.y));
            const uint32_t v1 = score_round2((a.z + b.z) + (c.z + d.z), (a.w + b.w) + (c.w + d.w));
            s[i] = make_float4(bf_lo(v0), bf_hi(v0), bf_lo(v1), bf_hi(v1));
            mt[i] = fmaxf(fmaxf(s[i].x, s[i].y), fmaxf(s[i].z, s[i].w));
        }
#pragma unroll
        for (int o = 1; o < 8; o <<= 1)
#pragma unroll
            for (int i = 0; i < 4; i++) mt[i] = fmaxf(mt[i], __shfl_xor_sync(0xffffffffu, mt[i], o));
#pragma unroll
        for (int i = 0; i < 4; i++) {
            const int head = 16 * w + 4 * i + mat;
            const float m_new = fmaxf(m_run[i], mt[i]);
            const float al = ex2((m_run[i] - m_new) * LOG2E);
            const float e0 = ex2((s[i].x - m_new) * LOG2E), e1 = ex2((s[i].y - m_new) * LOG2E);
            const float e2 = ex2((s[i].z - m_new) * LOG2E), e3 = ex2((s[i].w - m_new) * LOG2E);
            l_run[i] = l_run[i] * al + (e0 + e1) + (e2 + e3);
            m_run[i] = m_new;
            *(uint2*)(smem + OFF_AP + (k & 1) * 2560 + head * 80 + r * 8) = make_uint2(pack_bf16(e0, e1), pack_bf16(e2, e3));
            if (r == 0) ((float*)(smem + OFF_AALPHA))[(k & 1) * 32 + head] = al;
        }
        bar_arrive(BAR_P, 320);
    }
#pragma unroll
    for (int i = 0; i < 4; i++) {
        float l = l_run[i];
        l += __shfl_xor_sync(0xffffffffu, l, 1);
        l += __shfl_xor_sync(0xffffffffu, l, 2);
        l += __shfl_xor_sync(0xffffffffu, l, 4);
        if (r == 0) p.sc->ml[((16 * w + 4 * i + mat) * SPLIT + asp) * 4 + ab] = make_float2(m_run[i], l);
    }
    bar_arrive(BAR_E, 320);
}

__device__ __forceinline__ void attention_A(const Params& p, char* smem, int sw, int lane, int ab, int asp, bool idle_before) {
    const uint32_t sbase = smem_u32(smem);
    const int tid = sw * 32 + lane;
    const int g = lane >> 2, t = lane & 3, mat = lane >> 3, r = lane & 7;
    const int mi = sw & 1, cq = sw >> 1;
    uint4 qf[8];
    {
        const unsigned* src = p.sc->qabs + ab * 8192 + sw * 1024 + lane * 4;
        for (int k = 0; k < (idle_before ? TUNED(ASLEEP) : TUNED(ASLEEP2)); k++) __nanosleep(1000);
        ll_poll4(qf, src, 128, 500);
        if (sw == 0) PROF(6);
    }
    bar_sync(BAR_S, NSW * 32);
    float oacc[2][8][4];
#pragma unroll
    for (int a = 0; a < 2; a++)
#pragma unroll
        for (int b = 0; b < 8; b++) zero4(oacc[a][b]);
    float* red = (float*)(smem + OFF_ARED) + (cq * 32 + 16 * mi + g) * 40 + 2 * t;
    const uint32_t qk_off = sbase + 2 * cq * 4096 + ((mat >> 1) * 8 + r) * 128 + (((mat & 1) ^ r) << 4);
    const uint32_t pv_off = sbase + sw * 4096 + ((mat & 1) * 8 + r) * 128 + (((mat >> 1) ^ r) << 4);
    const uint32_t p_off = sbase + OFF_AP + ((mat & 1) * 8 + r) * 80 + (mat >> 1) * 16;
    int st = 0, ph = 0, stp = 0;
    for (int k = -1; k < ATILES; k++) {
        float sacc[4][4];
        if (k + 1 < ATILES) {
            mbar_wait(sbase + OFF_BAR + (MB_AFULL + st) * 8, ph);
            if (k == -1 && sw == 0) PROF(13);
#pragma unroll
            for (int a = 0; a < 4; a++) zero4(sacc[a]);
#pragma unroll
            for (int ks = 0; ks < 8; ks++) {
#pragma unroll
                for (int np = 0; np < 2; np++) {
                    uint32_t b0, b1, b2, b3;
                    ldsm4(b0, b1, b2, b3, (qk_off ^ ((ks & 3) << 5)) + st * 32768 + (ks >> 2) * 4096 + np * 2048);
                    mma(sacc[2 * np], qf[ks].x, qf[ks].y, qf[ks].z, qf[ks].w, b0, b1);
                    mma(sacc[2 * np + 1], qf[ks].x, qf[ks].y, qf[ks].z, qf[ks].w, b2, b3);
                }
            }
        }
        if (k >= 0) bar_sync(BAR_P, 320);
        if (k + 1 < ATILES) {
#pragma unroll
            for (int nt = 0; nt < 4; nt++) {
                *(float2*)(red + 8 * nt) = make_float2(sacc[nt][0], sacc[nt][1]);
                *(float2*)(red + 8 * nt + 8 * 40) = make_float2(sacc[nt][2], sacc[nt][3]);
            }
            bar_arrive(BAR_R, 352);
        }
        if (k >= 0) {
            const float* alpha = (const float*)(smem + OFF_AALPHA) + (k & 1) * 32;
            const float al0 = alpha[g], al1 = alpha[g + 8], al2 = alpha[g + 16], al3 = alpha[g + 24];
            if (!__all_sync(0xffffffffu, al0 == 1.f && al1 == 1.f && al2 == 1.f && al3 == 1.f)) {
#pragma unroll
                for (int nt = 0; nt < 8; nt++) {
                    oacc[0][nt][0] *= al0; oacc[0][nt][1] *= al0; oacc[0][nt][2] *= al1; oacc[0][nt][3] *= al1;
                    oacc[1][nt][0] *= al2; oacc[1][nt][1] *= al2; oacc[1][nt][2] *= al3; oacc[1][nt][3] *= al3;
                }
            }
#pragma unroll
            for (int ks = 0; ks < 2; ks++) {
                uint32_t pa[2][4];
#pragma unroll
                for (int mt = 0; mt < 2; mt++)
                    ldsm4(pa[mt][0], pa[mt][1], pa[mt][2], pa[mt][3], p_off + (k & 1) * 2560 + mt * 16 * 80 + ks * 32);
#pragma unroll
                for (int np = 0; np < 4; np++) {
                    uint32_t b0, b1, b2, b3;
                    ldsm4t(b0, b1, b2, b3, (pv_off ^ (np << 5)) + stp * 32768 + ks * 2048);
#pragma unroll
                    for (int mt = 0; mt < 2; mt++) {
                        mma(oacc[mt][2 * np], pa[mt][0], pa[mt][1], pa[mt][2], pa[mt][3], b0, b1);
                        mma(oacc[mt][2 * np + 1], pa[mt][0], pa[mt][1], pa[mt][2], pa[mt][3], b2, b3);
                    }
                }
            }
        }
        stp = st;
        if (++st == ASTAGES) { st = 0; ph ^= 1; }
    }
    if (sw == 0) PROF(14);
    {
        float dep = 0.f;
#pragma unroll
        for (int nt = 0; nt < 8; nt++) dep += oacc[1][nt][0];
        warp_release(sbase + OFF_BAR + MB_F3 * 8, lane, dep);
    }
#pragma unroll
    for (int mt = 0; mt < 2; mt++)
#pragma unroll
        for (int hh = 0; hh < 2; hh++) {
            float4* op = (float4*)(p.sc->opart + ((16 * mt + 8 * hh + g) * SPLIT + asp) * 2048 + sw * 256 + ab * 64) + t;
#pragma unroll
            for (int q = 0; q < 4; q++)
                op[4 * q] = make_float4(oacc[mt][2 * q][2 * hh], oacc[mt][2 * q][2 * hh + 1],
                                    oacc[mt][2 * q + 1][2 * hh], oacc[mt][2 * q + 1][2 * hh + 1]);
        }
    bar_sync(BAR_E, 320);
    if (tid == 0) signal_counter(&p.sc->cnt);
    if (sw == 0) PROF(7);
}

__device__ __forceinline__ float matvec64(char* smem, const uint32_t (&xf)[4][2], int mb_full, int mb_free, int sw, int lane) {
    const uint32_t sbase = smem_u32(smem);
    const int g = lane >> 2, t = lane & 3, mat = lane >> 3, r = lane & 7;
    const uint32_t a = sbase + BLK_W + sw * 8192 + ((mat >> 1) * 8 + r) * 128 + (((mat & 1) ^ r) << 4);
    float c[4][4];
#pragma unroll
    for (int mt = 0; mt < 4; mt++) zero4(c[mt]);
    mbar_wait(sbase + OFF_BAR + (mb_full + (sw >> 1)) * 8, 0);
#pragma unroll
    for (int ks = 0; ks < 4; ks++)
#pragma unroll
        for (int mt = 0; mt < 4; mt++) {
            uint32_t a0, a1, a2, a3;
            ldsm4t(a0, a1, a2, a3, (a ^ (mt << 5)) + ks * 2048);
            mma(c[mt], a0, a1, a2, a3, xf[ks][0], xf[ks][1]);
        }
    warp_release(sbase + OFF_BAR + mb_free * 8, lane, (c[0][0] + c[1][0]) + (c[2][0] + c[3][0]));
    float* rp = (float*)(smem + OFF_RED);
#pragma unroll
    for (int mt = 0; mt < 4; mt++) {
        const float y0 = (t < 2 ? c[mt][0] : c[mt][2]) + __shfl_xor_sync(0xffffffffu, t < 2 ? c[mt][2] : c[mt][0], 2);
        const float y1 = (t < 2 ? c[mt][1] : c[mt][3]) + __shfl_xor_sync(0xffffffffu, t < 2 ? c[mt][3] : c[mt][1], 2);
        float* d = rp + sw * 256 + (t & 1) * 128 + 16 * mt + (t >> 1) * 8 + g;
        d[0] = y0;
        d[64] = y1;
    }
    bar_sync(BAR_S, NSW * 32);
    float y = 0.f;
#pragma unroll
    for (int i = 0; i < NSW; i++) y += rp[i * 256 + sw * 32 + lane];
    return y;
}
__device__ __forceinline__ void load_xfrags(const char* smem, uint32_t (&xf)[4][2], int sw, int lane) {
    const uint32_t* x32 = (const uint32_t*)(smem + OFF_X) + ((lane >> 2) & 3) * 256 + 32 * sw + (lane & 3);
#pragma unroll
    for (int ks = 0; ks < 4; ks++) {
        xf[ks][0] = lane < 16 ? x32[ks * 8] : 0u;
        xf[ks][1] = lane < 16 ? x32[ks * 8 + 4] : 0u;
    }
}
__device__ __forceinline__ int vec_word(int vid, int tid) { return (tid >> 6) * 2048 + (vid >> 1) * 32 + ((tid & 63) >> 1); }
__device__ __forceinline__ void store_vec(unsigned* dst, int vid, int tid, float y) {
    const float y1 = __shfl_down_sync(0xffffffffu, y, 1);
    if (!(tid & 1)) ll_store(dst + vec_word(vid, tid), pack_bf16(y, y1));
}
__device__ __forceinline__ void fill_qtab(const Params& p, char* smem, bool isA, int wk, int vid, int tid) {
    const int r = 1 + (tid >> 4);
    uint4 v[1];
    const bool used = (!isA || r >= R_JOIN) && (vid >= 0 || r < R_LATE);
    const int pair = chunk_of(used ? r : R_JOIN, wk, vid) >> 4;
    ll_poll4(v, p.sc->qB + pair * 64 + (tid & 15) * 4, 0, 300);
    *(uint4*)(smem + OFF_Q + 256 + tid * 16) = v[0];
    __syncwarp();
    if ((tid & 31) == 0) mbar_expect_tx(smem_u32(smem) + OFF_BAR + MB_Q * 8, 0);
}
__device__ __forceinline__ void clear_handoffs(const Params& p, int vid, int tid) {
    const int chunk = chunk_of(R_LATE, 0, vid);
    if (tid < 32) *(uint4*)(p.sc->part + chunk * 128 + tid * 4) = make_uint4(0, 0, 0, 0);
    if (tid == 32) *(uint2*)(p.sc->pml + chunk * 2) = make_uint2(0, 0);
    if ((tid >> 4) == 4 && vid < 120) *(uint4*)(p.sc->oB + early_pair(vid) * 64 + (tid & 15) * 4) = make_uint4(0, 0, 0, 0);
    if ((tid >> 2) == 24) *(uint4*)(p.out + vid * 32 + (tid & 3) * 8) = make_uint4(0, 0, 0, 0);
    if (!((vid | tid) & 1)) p.sc->ctx[vec_word(vid, tid)] = 0;
}
__device__ __forceinline__ void side_prologue(const Params& p, char* smem, bool isA, int wk, int vid, int sw, int lane) {
    const uint32_t sbase = smem_u32(smem);
    const uint32_t bars = sbase + OFF_BAR;
    const int h = vid & 31, j = vid >> 5;
    const int tid = sw * 32 + lane;
    const int g = lane >> 2, t = lane & 3, mat = lane >> 3, r = lane & 7;
    {
        uint32_t xf[4][2];
        mbar_wait(bars + MB_X * 8, 0);
        load_xfrags(smem, xf, sw, lane);
        if (sw == 0) PROF(16);
        store_vec((vid & 1) ? p.sc->qA : p.sc->qB, vid, tid, matvec64(smem, xf, MB_SIDE + SI_WQ, MB_F0, sw, lane));
        if (sw == 0) PROF(18);
    }
    if (tid == 255) asm volatile("fence.acq_rel.gpu;" ::: "memory");
    __syncwarp();
    __nanosleep(TUNED(GSLEEP));
    if (tid < 64) {
        uint4 v[1];
        ll_poll4(v, p.sc->qA + (tid >> 4) * 2048 + h * 64 + (tid & 15) * 4, 0, 300);
        *(uint4*)(smem + OFF_VEC + (tid >> 4) * 272 + (tid & 15) * 16) = v[0];
    }
    fill_qtab(p, smem, isA, wk, vid, tid);
    bar_sync(BAR_S, NSW * 32);
    if (sw == 0) PROF(21);
    {
        mbar_wait(bars + (MB_SIDE + SI_WUK) * 8, 0);
        mbar_wait(bars + (MB_SIDE + SI_WUK + 1) * 8, 0);
        float c2[2][4];
        zero4(c2[0]); zero4(c2[1]);
        const uint32_t* qa = (const uint32_t*)(smem + OFF_VEC + (g & 3) * 272) + t;
        const uint32_t a = sbase + BLK_U + sw * 2048 + ((mat >> 1) * 8 + r) * 128 + (((mat & 1) ^ r) << 4);
#pragma unroll
        for (int ks = 0; ks < 8; ks++) {
            uint32_t b0, b1, b2, b3;
            ldsm4(b0, b1, b2, b3, (a ^ ((ks & 3) << 5)) + (ks >> 2) * 16384);
            const uint32_t a0 = qa[ks * 8], a2 = qa[ks * 8 + 4];
            mma(c2[0], a0, 0, a2, 0, b0, b1);
            mma(c2[1], a0, 0, a2, 0, b2, b3);
        }
        warp_release(bars + MB_FU * 8, lane, c2[0][0] + c2[1][0]);
        ll_store(p.sc->qabs + qabs_word(g & 3, h, j, sw, g >> 2, t),
                 g < 4 ? pack_bf16(c2[0][0], c2[0][1]) : pack_bf16(c2[1][0], c2[1][1]));
    }
    if (sw == 0) PROF(5);
}

__device__ __forceinline__ void side_epilogue(const Params& p, char* smem, int vid, int sw, int lane) {
    const uint32_t sbase = smem_u32(smem);
    const uint32_t bars = sbase + OFF_BAR;
    const int tid = sw * 32 + lane;
    const int g = lane >> 2, t = lane & 3;
    mbar_wait(bars + MB_CNT * 8, 0);
    if (sw == 0) PROF(8);
    if (vid & 1) {
        for (int k = 0; k < TUNED(CTXSLEEP); k++) __nanosleep(1000);
    } else {
        uint32_t of[4][2];
        const int h = vid >> 2;
        const int b = g & 3, sp = g >> 2;
        float wgt[SPLIT / 2];
        {
            float2 ml[SPLIT / 2];
            float M = -INFINITY, L = 0.f;
#pragma unroll
            for (int q = 0; q < SPLIT / 2; q++) { ml[q] = __ldcg(&p.sc->ml[(h * SPLIT + sp + 2 * q) * 4 + b]); M = fmaxf(M, ml[q].x); }
            M = fmaxf(M, __shfl_xor_sync(0xffffffffu, M, 16));
#pragma unroll
            for (int q = 0; q < SPLIT / 2; q++) { wgt[q] = ex2((ml[q].x - M) * LOG2E); L = fmaf(wgt[q], ml[q].y, L); }
            L += __shfl_xor_sync(0xffffffffu, L, 16);
#pragma unroll
            for (int q = 0; q < SPLIT / 2; q++) { wgt[q] /= L; mbar_wait(bars + (MB_SIDE + SI_OPART + q) * 8, 0); }
        }
#pragma unroll
        for (int ks = 0; ks < 4; ks++) {
            float v[4] = {0.f, 0.f, 0.f, 0.f};
#pragma unroll
            for (int q = 0; q < SPLIT / 2; q++) {
                const float4 u = *((const float4*)(smem + BLK_U) + (sp + 2 * q) * 512 + sw * 64 + b * 16 + 4 * ks + t);
                v[0] = fmaf(u.x, wgt[q], v[0]); v[1] = fmaf(u.y, wgt[q], v[1]);
                v[2] = fmaf(u.z, wgt[q], v[2]); v[3] = fmaf(u.w, wgt[q], v[3]);
            }
#pragma unroll
            for (int e = 0; e < 4; e++) v[e] += __shfl_xor_sync(0xffffffffu, v[e], 16);
#pragma unroll
            for (int hh = 0; hh < 2; hh++) {
                const uint32_t hi = pack_bf16(v[2 * hh], v[2 * hh + 1]);
                of[ks][hh] = sp == 0 ? hi : pack_bf16(v[2 * hh] - bf_lo(hi), v[2 * hh + 1] - bf_hi(hi));
            }
        }
        store_vec(p.sc->ctx, vid, tid, matvec64(smem, of, MB_SIDE + SI_WE, MB_F2, sw, lane));
        if (sw == 0) PROF(9);
    }
    const bool isB = !(vid & 1), late = isB && tid >= 240;
    const unsigned* xs = (isB ? p.sc->oB : p.sc->ctx) + (tid >> 6) * 2048 + (vid >> 4) * 256 + (tid & 63) * 4;
    const uint32_t* x32 = (const uint32_t*)(smem + OFF_X) + (g & 3) * XROW + t;
    const uint32_t wa = sbase + BLK_W + lane * 128 + ((sw ^ (lane & 7)) << 4);
    uint32_t* out = (uint32_t*)(p.out + (g & 3) * 1024 + (isB ? 512 : 0) + ((vid >> 1) & 7) * 64 + 8 * sw) + t;
    const unsigned* lp = p.sc->part + late_pair(vid) * 2048 + g * 128 + 16 * sw + 4 * t;
    const unsigned* lm = p.sc->pml + late_pair(vid) * 32 + 2 * g;
    __nv_bfloat16* lx = (__nv_bfloat16*)(smem + OFF_X) + 2 * (3 * XROW + 192) + 16 * t + sw + (lane & 8) + 4 * (lane & 16);
#pragma unroll 1
    for (int pass = 0; pass < 2; pass++) {
        const uint32_t wo = bars + (pass ? MB_SIDE + SI_WO : MB_SIDE + SI_WQ) * 8;
        mbar_wait(bars + (pass && isB ? MB_GO : MB_CNT) * 8, 0);
        uint4 v = make_uint4(1, 1, 1, 1);
        for (unsigned spins = 0;; spins++) {
            if (pass && !late) v = ll_load4(xs);
            if (ll_ok4(v)) break;
            __nanosleep(300);
            if (spins > SPIN_LIMIT) __trap();
        }
        __syncwarp();
        if (!late) *(uint4*)(smem + OFF_X + (tid >> 6) * (4 * XROW) + (tid & 63) * 16) = make_uint4(~v.x, ~v.y, ~v.z, ~v.w);
        bar_sync(BAR_S, NSW * 32);
        if (sw == 0) PROF(15);
        float acc[4][4];
#pragma unroll
        for (int k = 0; k < 4; k++) zero4(acc[k]);
        uint4 u0 = make_uint4(1, 1, 1, 1), u1 = u0;
        uint2 m0 = make_uint2(1, 1), m1 = m0;
#pragma unroll
        for (int q = 0; q < 4; q++) {
            if (q == 1 && isB) {
                const int z = lds_volatile(sbase + OFF_WIN + 4) + TUNED(TRIG) * TUNED(TAU) / 4;
                for (int k = pass ? 0 : 63; k < 64 && !__any_sync(0xffffffffu, (int)(now_ns() - z) >= 0); k++) __nanosleep(20);
                if (sw == 0) PROF(27);
                if (pass) { m0 = ll_load2(lm); m1 = ll_load2(lm + 16); u0 = ll_load4(lp); u1 = ll_load4(lp + 1024); }
            }
            if (q == 3) bar_sync(BAR_S, NSW * 32);
            uint32_t xf[16];
#pragma unroll
            for (int k = 0; k < 16; k++) xf[k] = x32[64 * q + 4 * k];
            mbar_wait(wo + q * 8, 0);
            if (q == 3 && sw == 0) PROF(11);
#pragma unroll
            for (int k = 0; k < 4; k++) {
                uint32_t b0, b1, b2, b3;
                ldsm4t(b0, b1, b2, b3, wa + q * TILE_BYTES + k * 4096);
                mma(acc[(2 * k) & 3], xf[4 * k], 0, xf[4 * k + 1], 0, b0, b1);
                mma(acc[(2 * k + 1) & 3], xf[4 * k + 2], 0, xf[4 * k + 3], 0, b2, b3);
            }
            if (q == 1 && isB) {
                for (unsigned spins = 0; !__all_sync(0xffffffffu, ll_ok4(u0) && ll_ok4(u1) && ll_ok4(make_uint4(m0.x, m0.y, m1.x, m1.y))); spins++) {
                    if (sw == 0 && spins < 3) PROF2(150 + spins);
                    m0 = ll_load2(lm); m1 = ll_load2(lm + 16); u0 = ll_load4(lp); u1 = ll_load4(lp + 1024);
                    if (spins > SPIN_LIMIT) __trap();
                }
                if (sw == 0) PROF2(153);
                const float a0 = __uint_as_float(~m0.x), a1 = __uint_as_float(~m1.x), M = redux_max(fmaxf(a0, a1));
                const float w0 = ex2((a0 - M) * LOG2E), w1 = ex2((a1 - M) * LOG2E);
                float l = w0 * __uint_as_float(~m0.y) + w1 * __uint_as_float(~m1.y);
                const float o0 = w0 * __uint_as_float(~u0.x) + w1 * __uint_as_float(~u1.x), o1 = w0 * __uint_as_float(~u0.y) + w1 * __uint_as_float(~u1.y);
                const float o2 = w0 * __uint_as_float(~u0.z) + w1 * __uint_as_float(~u1.z), o3 = w0 * __uint_as_float(~u0.w) + w1 * __uint_as_float(~u1.w);
                const bool hi = lane & 16, mid = lane & 8;
                const float e0 = (hi ? o2 : o0) + __shfl_xor_sync(0xffffffffu, hi ? o0 : o2, 16);
                const float e1 = (hi ? o3 : o1) + __shfl_xor_sync(0xffffffffu, hi ? o1 : o3, 16);
                l += __shfl_xor_sync(0xffffffffu, l, 16);
                float e = (mid ? e1 : e0) + __shfl_xor_sync(0xffffffffu, mid ? e0 : e1, 8);
                l += __shfl_xor_sync(0xffffffffu, l, 8);
                e += __shfl_xor_sync(0xffffffffu, e, 4);
                l += __shfl_xor_sync(0xffffffffu, l, 4);
                *lx = __float2bfloat16_rn(__fdividef(e, l));
                if (pass && sw == 0 && !(vid & 15)) *(uint2*)(p.sc->qB + late_pair(vid) * 64 + 2 * lane) = make_uint2(0, 0);
                if (sw == 0) PROF(4);
            }
        }
        const uint32_t y = pack_bf16((acc[0][0] + acc[1][0]) + (acc[2][0] + acc[3][0]), (acc[0][1] + acc[1][1]) + (acc[2][1] + acc[3][1]));
        asm volatile("{\n .reg .pred q;\n setp.ne.u32 q, %2, 0;\n @q red.relaxed.gpu.global.add.noftz.bf16x2 [%0], %1;\n}"
                     ::"l"(out), "r"(y), "r"((int)(pass && lane < 16)) : "memory");
    }
    if (sw == 7) PROF(25);
}

__global__ void __launch_bounds__(NTHREADS, 1) fused_decode_kernel(const Ptrs ptrs, const __grid_constant__ Maps maps) {
    extern __shared__ __align__(1024) char smem[];
    Params p;
    static_cast<Ptrs&>(p) = ptrs;
    p.tm = maps.tm;
    const unsigned blk = blockIdx.x;
    if (threadIdx.x == 0) first_load(p, smem_u32(smem), blk);
    const int warp = __shfl_sync(0xffffffffu, threadIdx.x >> 5, 0), lane = threadIdx.x & 31;
    const bool isA = blk % APER == APER - 1;
    const int aidx = blk / APER, ab = aidx / SPLIT, asp = aidx % SPLIT;
    const int wk = isA ? NB + aidx : blk - aidx;
    const int vid = !isA ? wk : asp == 3 ? -1 : NB + ab * 3 + asp;
    if (threadIdx.x == 32) next_loads(p, smem_u32(smem), vid);
    if (lane == 0 && warp != 1) {
        const int wu = max(warp, 1);
#pragma unroll
        for (int k = 0; k < (MB_COUNT - MB_EARLY + 10) / 11; k++) {
            const int i = MB_EARLY + k * 11 + wu - 1;
            if (i < MB_COUNT && i != MB_FULL) mbar_init(smem_u32(smem) + OFF_BAR + i * 8, i >= MB_F0 ? NSW : 1);
        }
        fence_mbar_init();
        if (wu >= 2 && wu < 7) asm volatile("prefetch.tensormap [%0];" ::"l"(&p.tm[wu]) : "memory");
    }
    __syncwarp();
    if (threadIdx.x == 33) {
        *(int2*)(smem + OFF_DONE) = make_int2(0, 0);
        *(int2*)(smem + OFF_WIN) = make_int2(TUNED(WSTART), 0);
    }
    if (warp >= 4 && vid >= 0) clear_handoffs(p, vid, threadIdx.x - 128);
    bar_sync(0, NTHREADS);
    if (warp == 0) {
        produce(p, smem, lane, isA, wk, vid, ab * 4096 + asp * 32);
    } else if (warp < 3) {
        if (isA) softmax_A(p, smem, warp - 1, lane, ab, asp);
        consume(p, smem, isA, wk, vid, warp - 1, lane);
    } else if (warp == 3) {
        service(p, smem, isA, vid, lane);
    } else {
        const int sw = warp - 4;
        if (vid >= 0) side_prologue(p, smem, isA, wk, vid, sw, lane);
        if (isA) attention_A(p, smem, sw, lane, ab, asp, vid < 0);
        if (vid < 0) fill_qtab(p, smem, isA, wk, vid, threadIdx.x - 128);
        if (vid >= 0) side_epilogue(p, smem, vid, sw, lane);
    }
}

__device__ float g_tmp[2][4 * 32 * 512];
__device__ __forceinline__ float bfr(float x) { return __bfloat162float(__float2bfloat16_rn(x)); }
template <typename X>
__global__ void fb_matvec(const X* x, int xb, int xh, int K, const __nv_bfloat16* W, int wk, int wh, int wn, float* y,
                          __nv_bfloat16* out, bool round) {
    const int n = threadIdx.x, h = blockIdx.x, b = blockIdx.y;
    float s = 0.f;
    for (int k = 0; k < K; k++) s += (float)x[b * xb + h * xh + k] * __bfloat162float(W[(size_t)k * wk + h * wh + (size_t)n * wn]);
    if (out) out[b * 1024 + n] = __float2bfloat16_rn(s);
    else y[(b * gridDim.x + h) * blockDim.x + n] = round ? bfr(s) : s;
}
__global__ void fb_attn(const float* q, const __nv_bfloat16* K, const __nv_bfloat16* V, int D, size_t sb, size_t sh, float* o, bool round) {
    __shared__ float sc[4096], red[8];
    const int h = blockIdx.x, b = blockIdx.y, tid = threadIdx.x;
    K += b * sb + h * sh; V += b * sb + h * sh; q += (b * 32 + h) * D;
    float m = -INFINITY, l = 0.f;
    for (int k = tid; k < 4096; k += 256) {
        float s = 0.f;
        for (int d = 0; d < D; d++) s += q[d] * __bfloat162float(K[(size_t)k * D + d]);
        m = fmaxf(m, sc[k] = bfr(bfr(s) * SCALE));
    }
    m = warp_max(m);
    if (!(tid & 31)) red[tid >> 5] = m;
    __syncthreads();
    for (int i = 0; i < 8; i++) m = fmaxf(m, red[i]);
    __syncthreads();
    for (int k = tid; k < 4096; k += 256) { const float e = expf(sc[k] - m); l += e; sc[k] = bfr(e); }
    l = warp_sum(l);
    if (!(tid & 31)) red[tid >> 5] = l;
    __syncthreads();
    l = 0.f;
    for (int i = 0; i < 8; i++) l += red[i];
    for (int d = tid; d < D; d += 256) {
        float s = 0.f;
        for (int k = 0; k < 4096; k++) s += sc[k] * __bfloat162float(V[(size_t)k * D + d]);
        o[(b * 32 + h) * D + d] = round ? bfr(s / l) : s / l;
    }
}
void launch_fallback(void* const* d_in, __nv_bfloat16* out) {
    typedef const __nv_bfloat16* BP;
    float* t0;
    cudaGetSymbolAddress((void**)&t0, g_tmp);
    float* t1 = t0 + 4 * 32 * 512;
    const dim3 gh(32, 4), g1(1, 4);
    fb_matvec<<<gh, 128>>>((BP)d_in[0], 512, 0, 512, (BP)d_in[2], 4096, 128, 1, t0, nullptr, true);
    fb_matvec<<<gh, 512>>>((const float*)t0, 4096, 128, 128, (BP)d_in[3], 1, 128, 4096, t1, nullptr, true);
    fb_attn<<<gh, 256>>>(t1, (BP)d_in[1], (BP)d_in[1], 512, (size_t)4096 * 512, 0, t0, false);
    fb_matvec<<<gh, 128>>>((const float*)t0, 32 * 512, 512, 512, (BP)d_in[4], 4096, 128, 1, t1, nullptr, true);
    fb_matvec<<<g1, 512>>>((const float*)t1, 4096, 0, 4096, (BP)d_in[5], 512, 0, 1, nullptr, out, false);
    fb_matvec<<<gh, 128>>>((BP)d_in[6], 512, 0, 512, (BP)d_in[9], 4096, 128, 1, t0, nullptr, true);
    fb_attn<<<gh, 256>>>(t0, (BP)d_in[7], (BP)d_in[8], 128, (size_t)32 * 4096 * 128, (size_t)4096 * 128, t1, true);
    fb_matvec<<<g1, 512>>>((const float*)t1, 4096, 0, 4096, (BP)d_in[10], 512, 0, 1, nullptr, out + 512, false);
}

typedef CUresult (*EncodeFn)(CUtensorMap*, CUtensorMapDataType, cuuint32_t, void*, const cuuint64_t*, const cuuint64_t*,
                             const cuuint32_t*, const cuuint32_t*, CUtensorMapInterleave, CUtensorMapSwizzle,
                             CUtensorMapL2promotion, CUtensorMapFloatOOBfill);

void make_map(EncodeFn enc, CUtensorMap* tm, void* ptr, uint64_t cols, uint64_t rows, uint32_t br) {
    const cuuint64_t dims[2] = {cols, rows};
    const cuuint64_t strides[1] = {cols * 2};
    const cuuint32_t box[2] = {64, br};
    const cuuint32_t es[2] = {1, 1};
    enc(tm, CU_TENSOR_MAP_DATA_TYPE_BFLOAT16, 2, ptr, dims, strides, box, es, CU_TENSOR_MAP_INTERLEAVE_NONE,
        CU_TENSOR_MAP_SWIZZLE_128B, CU_TENSOR_MAP_L2_PROMOTION_NONE,
        CU_TENSOR_MAP_FLOAT_OOB_FILL_NONE);
}

}

extern "C" void kernel_launch(void* const* d_in, const int* in_sizes, int n_in, void* d_out, int out_size) {
    (void)in_sizes; (void)n_in; (void)out_size;
    void* fn = nullptr;
    cudaDriverEntryPointQueryResult qr;
    cudaGetDriverEntryPoint("cuTensorMapEncodeTiled", &fn, cudaEnableDefault, &qr);
    EncodeFn enc = (EncodeFn)fn;
    int dev = 0, sms = 0, per_sm = 0;
    cudaGetDevice(&dev);
    cudaDeviceGetAttribute(&sms, cudaDevAttrMultiProcessorCount, dev);
    cudaFuncSetAttribute(fused_decode_kernel, cudaFuncAttributeMaxDynamicSharedMemorySize, SMEM_BYTES);
    cudaOccupancyMaxActiveBlocksPerMultiprocessor(&per_sm, fused_decode_kernel, NTHREADS, SMEM_BYTES);
    if (!enc || sms * per_sm < NCTA) {
        launch_fallback(d_in, (__nv_bfloat16*)d_out);
        return;
    }
    Ptrs p;
    Maps m;
    make_map(enc, &m.tm[0], d_in[9], 4096, 512, 128);
    make_map(enc, &m.tm[1], d_in[2], 4096, 512, 128);
    make_map(enc, &m.tm[2], d_in[10], 512, 4096, 128);
    make_map(enc, &m.tm[3], d_in[5], 512, 4096, 128);
    make_map(enc, &m.tm[4], d_in[3], 4096, 512, 128);
    make_map(enc, &m.tm[5], d_in[4], 4096, 512, 128);
    make_map(enc, &m.tm[6], d_in[1], 512, 4 * 4096, 32);
    p.xA = (const __nv_bfloat16*)d_in[0];
    p.xB = (const __nv_bfloat16*)d_in[6];
    p.K = (const __nv_bfloat16*)d_in[7];
    p.V = (const __nv_bfloat16*)d_in[8];
    p.out = (__nv_bfloat16*)d_out;
    cudaGetSymbolAddress((void**)&p.sc, g_scratch);
    fused_decode_kernel<<<NCTA, NTHREADS, SMEM_BYTES>>>(p, m);
}
```

```cpp
#include <cuda.h>
#include <cuda_runtime.h>
#include <cuda_bf16.h>
#include <stdint.h>

namespace {

#define TV_WSTART 3
#define TV_WMIN0 3
#define TV_WMIN 2
#define TV_IMIN 100
#define TV_LEAD 18
#define TV_LEADE 14
#define TV_WMAXE 3
#define TV_IEND 120
#define TV_TAU 650
#define TV_GAIN 1
#define TV_JUMP 400
#define TV_STAG 80
#define TV_QSLEEP 1800
#define TV_GSLEEP 3000
#define TV_ASLEEP 16
#define TV_ASLEEP2 8
#define TV_ITE 12
#define TV_WESTEP 8
#define TV_CNT0 56
#define TV_CTXSLEEP 8
#define TV_MERGE 2
#define TV_MERGE0 6
#define TV_SVC 64
#define TV_GO 1
#define TV_TRIG 541
enum { T_WSTART, T_WMIN0, T_WMIN, T_IMIN, T_LEAD, T_LEADE, T_WMAXE, T_IEND, T_TAU, T_GAIN, T_JUMP, T_STAG, T_QSLEEP, T_GSLEEP, T_ASLEEP, T_ASLEEP2, T_ITE, T_WESTEP, T_CNT0, T_CTXSLEEP, T_MERGE, T_MERGE0, T_SVC, T_GO, T_TRIG, T_COUNT };
#define TUNED(k) (TV_##k)

constexpr int TK = 64;
constexpr int TILE_BYTES = TK * 256;
constexpr int NS = 6;
constexpr int WMAX = 6;
constexpr int NSW = 8;
constexpr int NTHREADS = (4 + NSW) * 32;
constexpr int SPLIT = 4;
constexpr int AKEYS = 4096 / SPLIT;
constexpr int ATILES = AKEYS / 32;
constexpr int ASTAGES = 6;
constexpr int NCTA = 132;
constexpr int APER = 8;
constexpr int NB = NCTA - 4 * SPLIT;
constexpr int R_JOIN = 12, R_LATE = 16, N_EARLY = 120;
static_assert(R_JOIN * NB + (R_LATE - R_JOIN) * NCTA == N_EARLY * 16, "early chunks");
constexpr int I_BOX = 8 * (R_LATE + 1);
__device__ __forceinline__ int late_pair(int vid) { return N_EARLY + (vid >> 4); }
__device__ __forceinline__ int chunk_of(int r, int wk, int vid) {
    return r * NB + max(r - R_JOIN, 0) * (NCTA - NB) + (r == R_LATE ? vid : wk);
}

#define CGRP 4
constexpr int CHUNK_STEP = CGRP * TILE_BYTES;
__device__ __forceinline__ size_t chunk_off(unsigned c) { return (size_t)(4 * c - 3 * (c % CGRP)) * TILE_BYTES; }

constexpr int OFF_RING = 0;
constexpr int OFF_SIDE = NS * TILE_BYTES;
constexpr int OFF_SCR = OFF_SIDE + 98304;
constexpr int OFF_X = OFF_SCR;
constexpr int XROW = 264;
constexpr int OFF_RED = OFF_SCR + 8192;
constexpr int OFF_ARED = OFF_SCR;
constexpr int OFF_AP = OFF_ARED + 4 * 32 * 40 * 4;
constexpr int OFF_AALPHA = OFF_AP + 2 * 32 * 80;
constexpr int OFF_OPART = OFF_AALPHA + 256;
constexpr int OFF_ML = OFF_OPART + 2 * 512;
constexpr int OFF_DONE = OFF_ML + 16;
constexpr int OFF_WIN = OFF_DONE + 8;
constexpr int OFF_VEC = OFF_WIN + 8;
constexpr int OFF_Q = OFF_VEC + 4 * 68 * 4;
constexpr int OFF_BAR = OFF_Q + (R_LATE + 1) * 256;
enum { SI_WQ = 0, SI_WUK = 4, SI_WE = 6, SI_OPART = 10, SI_WO = 12, SI_COUNT = SI_WO + 5 };
enum {
    MB_X = 0, MB_SIDE = 1, MB_EARLY = MB_SIDE + 4,
    MB_FULL = MB_SIDE + SI_COUNT,
    MB_AFULL = MB_FULL + NS,
    MB_CNT = MB_AFULL + ASTAGES,
    MB_GO,
    MB_EMPTY,
    MB_F0 = MB_EMPTY + NS, MB_FU, MB_F2, MB_F3,
    MB_Q,
    MB_COUNT
};
constexpr int SMEM_BYTES = OFF_BAR + MB_COUNT * 8;
static_assert(SMEM_BYTES <= 232448, "smem");
constexpr int BLK_W = OFF_SIDE;
constexpr int BLK_U = OFF_SIDE + 65536;

constexpr int BAR_B = 9  , BAR_S = 2, BAR_R = 5, BAR_P = 6, BAR_E = 7;

constexpr float SCALE = 0.08838834764831845f;
constexpr float LOG2E = 1.4426950408889634f;
constexpr unsigned SPIN_LIMIT = 1u << 22;

struct Scratch {
    float opart[32 * SPLIT * 2048];
    unsigned qB[4 * 2048];
    unsigned qA[4 * 2048];
    unsigned qabs[4 * 8192];
    unsigned ctx[4 * 2048];
    unsigned oB[4 * 2048];
    unsigned part[2048 * 128];
    unsigned pml[2048 * 2];
    float2 ml[32 * SPLIT * 4];
    unsigned prog, pad[31];
    unsigned cnt;
};
__device__ __align__(128) Scratch g_scratch;

struct Ptrs {
    const __nv_bfloat16 *K, *V, *xA, *xB;
    __nv_bfloat16* out;
    Scratch* sc;
};
struct Maps {
    CUtensorMap tm[7];
};
struct Params : Ptrs {
    const CUtensorMap* tm;
};

#define PROF(i)
#define PROF2(i)

__device__ __forceinline__ uint32_t smem_u32(const void* p) { return (uint32_t)__cvta_generic_to_shared(p); }
__device__ __forceinline__ void mbar_init(uint32_t bar, int cnt) {
    asm volatile("mbarrier.init.shared::cta.b64 [%0], %1;" ::"r"(bar), "r"(cnt) : "memory");
}
__device__ __forceinline__ void mbar_expect_tx(uint32_t bar, uint32_t bytes) {
    asm volatile("mbarrier.arrive.expect_tx.shared::cta.b64 _, [%0], %1;" ::"r"(bar), "r"(bytes) : "memory");
}
__device__ __forceinline__ bool mbar_try(uint32_t bar, uint32_t parity) {
    uint32_t ok;
    asm volatile("{\n .reg .pred p;\n mbarrier.try_wait.parity.shared::cta.b64 p, [%1], %2;\n selp.u32 %0, 1, 0, p;\n}"
                 : "=r"(ok) : "r"(bar), "r"(parity) : "memory");
    return ok;
}
__device__ __forceinline__ void mbar_wait(uint32_t bar, uint32_t parity) {
    unsigned spins = 0;
    while (!mbar_try(bar, parity))
        if (++spins > SPIN_LIMIT) __trap();
}
__device__ __forceinline__ bool mbar_test(uint32_t bar, uint32_t parity) {
    uint32_t ok;
    asm volatile("{\n .reg .pred p;\n mbarrier.test_wait.parity.shared::cta.b64 p, [%1], %2;\n selp.u32 %0, 1, 0, p;\n}"
                 : "=r"(ok) : "r"(bar), "r"(parity) : "memory");
    return ok;
}
__device__ __forceinline__ void warp_release(uint32_t bar, int lane, float dep) {
    const uint32_t any = __ballot_sync(0xffffffffu, dep != dep);
    if (lane == 0)
        asm volatile("{\n .reg .pred q;\n setp.eq.u32 q, %1, 0;\n @q mbarrier.arrive.shared::cta.b64 _, [%0];\n"
                     " @!q mbarrier.arrive.shared::cta.b64 _, [%0];\n}" ::"r"(bar), "r"(any) : "memory");
}
__device__ __forceinline__ bool elect_one() {
    uint32_t e;
    asm volatile("{\n .reg .pred p;\n elect.sync _|p, 0xffffffff;\n selp.u32 %0, 1, 0, p;\n}" : "=r"(e));
    return e;
}
__device__ __forceinline__ int lds_volatile(uint32_t addr) {
    int v;
    asm volatile("ld.volatile.shared.u32 %0, [%1];" : "=r"(v) : "r"(addr) : "memory");
    return v;
}
__device__ __forceinline__ int2 lds_volatile2(uint32_t addr) {
    int2 v;
    asm volatile("ld.volatile.shared.v2.u32 {%0, %1}, [%2];" : "=r"(v.x), "=r"(v.y) : "r"(addr) : "memory");
    return v;
}
__device__ __forceinline__ void sts_volatile2(uint32_t addr, int a, int b) {
    asm volatile("st.volatile.shared.v2.u32 [%0], {%1, %2};" ::"r"(addr), "r"(a), "r"(b) : "memory");
}
__device__ __forceinline__ void sts_volatile(uint32_t addr, int v) {
    asm volatile("st.volatile.shared.u32 [%0], %1;" ::"r"(addr), "r"(v) : "memory");
}
__device__ __forceinline__ unsigned now_ns() {
    unsigned t;
    asm volatile("mov.u32 %0, %%globaltimer_lo;" : "=r"(t) :: "memory");
    return t;
}
__device__ __forceinline__ int clock_after(unsigned dep) {
    int c;
    asm volatile("{\n .reg .pred q;\n setp.eq.u32 q, %1, 0;\n @q mov.u32 %0, %%globaltimer_lo;\n @!q mov.u32 %0, %%globaltimer_lo;\n}" : "=r"(c) : "r"(dep) : "memory");
    return c;
}
__device__ __forceinline__ void fence_mbar_init() { asm volatile("fence.mbarrier_init.release.cluster;" ::: "memory"); }
__device__ __forceinline__ uint64_t policy_evict_first() {
    uint64_t pol;
    asm volatile("createpolicy.fractional.L2::evict_first.b64 %0, 1.0;" : "=l"(pol));
    return pol;
}
__device__ __forceinline__ uint64_t policy_evict_normal() {
    uint64_t pol;
    asm volatile("createpolicy.fractional.L2::evict_normal.b64 %0, 1.0;" : "=l"(pol));
    return pol;
}
__device__ __forceinline__ void bulk_load(uint32_t dst, const void* src, uint32_t bytes, uint32_t bar, uint64_t pol) {
    asm volatile("cp.async.bulk.shared::cluster.global.mbarrier::complete_tx::bytes.L2::cache_hint [%0], [%1], %2, [%3], %4;"
                 ::"r"(dst), "l"(src), "r"(bytes), "r"(bar), "l"(pol) : "memory");
}
__device__ __forceinline__ void bulk_load_nohint(uint32_t dst, const void* src, uint32_t bytes, uint32_t bar) {
    asm volatile("cp.async.bulk.shared::cluster.global.mbarrier::complete_tx::bytes [%0], [%1], %2, [%3];"
                 ::"r"(dst), "l"(src), "r"(bytes), "r"(bar) : "memory");
}
__device__ __forceinline__ void tma2d_hint(uint32_t dst, const CUtensorMap* tm, int x, int y, uint32_t bar, uint64_t pol) {
    asm volatile("cp.async.bulk.tensor.2d.shared::cluster.global.mbarrier::complete_tx::bytes.L2::cache_hint [%0], [%1, {%3, %4}], [%2], %5;"
                 ::"r"(dst), "l"(tm), "r"(bar), "r"(x), "r"(y), "l"(pol) : "memory");
}
__device__ __forceinline__ void ldsm4(uint32_t& r0, uint32_t& r1, uint32_t& r2, uint32_t& r3, uint32_t addr) {
    asm volatile("ldmatrix.sync.aligned.m8n8.x4.shared.b16 {%0,%1,%2,%3}, [%4];"
                 : "=r"(r0), "=r"(r1), "=r"(r2), "=r"(r3) : "r"(addr) : "memory");
}
__device__ __forceinline__ void ldsm4t(uint32_t& r0, uint32_t& r1, uint32_t& r2, uint32_t& r3, uint32_t addr) {
    asm volatile("ldmatrix.sync.aligned.m8n8.x4.trans.shared.b16 {%0,%1,%2,%3}, [%4];"
                 : "=r"(r0), "=r"(r1), "=r"(r2), "=r"(r3) : "r"(addr) : "memory");
}
__device__ __forceinline__ void mma(float (&c)[4], uint32_t a0, uint32_t a1, uint32_t a2, uint32_t a3, uint32_t b0, uint32_t b1) {
    asm volatile("mma.sync.aligned.m16n8k16.row.col.f32.bf16.bf16.f32 {%0,%1,%2,%3}, {%4,%5,%6,%7}, {%8,%9}, {%0,%1,%2,%3};"
                 : "+f"(c[0]), "+f"(c[1]), "+f"(c[2]), "+f"(c[3])
                 : "r"(a0), "r"(a1), "r"(a2), "r"(a3), "r"(b0), "r"(b1));
}
__device__ __forceinline__ void zero4(float (&c)[4]) { c[0] = c[1] = c[2] = c[3] = 0.f; }
__device__ __forceinline__ void bar_sync(int id, int n) { asm volatile("bar.sync %0, %1;" ::"r"(id), "r"(n) : "memory"); }
__device__ __forceinline__ void bar_arrive(int id, int n) { asm volatile("bar.arrive %0, %1;" ::"r"(id), "r"(n) : "memory"); }
__device__ __forceinline__ float ex2(float x) { float y; asm("ex2.approx.ftz.f32 %0, %1;" : "=f"(y) : "f"(x)); return y; }
__device__ __forceinline__ uint32_t pack_bf16(float lo, float hi) {
    uint32_t r; asm("cvt.rn.bf16x2.f32 %0, %1, %2;" : "=r"(r) : "f"(hi), "f"(lo)); return r;
}
__device__ __forceinline__ float bf_lo(uint32_t u) { return __uint_as_float(u << 16); }
__device__ __forceinline__ float bf_hi(uint32_t u) { return __uint_as_float(u & 0xffff0000u); }
__device__ __forceinline__ uint32_t score_round2(float a, float b) {
    const uint32_t u = pack_bf16(a, b);
    return pack_bf16(bf_lo(u) * SCALE, bf_hi(u) * SCALE);
}
__device__ __forceinline__ float warp_max(float v) {
#pragma unroll
    for (int o = 16; o > 0; o >>= 1) v = fmaxf(v, __shfl_xor_sync(0xffffffffu, v, o));
    return v;
}
__device__ __forceinline__ float redux_max(float v) {
    const int i = __float_as_int(v), m = __reduce_max_sync(0xffffffffu, i ^ ((i >> 31) & 0x7fffffff));
    return __int_as_float(m ^ ((m >> 31) & 0x7fffffff));
}
__device__ __forceinline__ float warp_sum(float v) {
#pragma unroll
    for (int o = 16; o > 0; o >>= 1) v += __shfl_xor_sync(0xffffffffu, v, o);
    return v;
}

__device__ __forceinline__ void ll_store(unsigned* p, unsigned bits) {
    unsigned u = ~bits;
    u = u ? u : 0x80008000u;
    asm volatile("st.relaxed.gpu.global.u32 [%0], %1;" ::"l"(p), "r"(u) : "memory");
}
__device__ __forceinline__ void ll_store2(unsigned* p, unsigned a, unsigned b) {
    unsigned u = ~a, v = ~b;
    u = u ? u : 0x80008000u;
    v = v ? v : 0x80008000u;
    asm volatile("st.relaxed.gpu.global.v2.u32 [%0], {%1, %2};" ::"l"(p), "r"(u), "r"(v) : "memory");
}
__device__ __forceinline__ void ll_store4(unsigned* p, float a, float b, float c, float d) {
    unsigned u[4] = {~__float_as_uint(a), ~__float_as_uint(b), ~__float_as_uint(c), ~__float_as_uint(d)};
#pragma unroll
    for (int k = 0; k < 4; k++) u[k] = u[k] ? u[k] : 0x80008000u;
    asm volatile("st.relaxed.gpu.global.v4.u32 [%0], {%1, %2, %3, %4};" ::"l"(p), "r"(u[0]), "r"(u[1]), "r"(u[2]), "r"(u[3]) : "memory");
}
__device__ __forceinline__ unsigned ll_load(const unsigned* p) {
    unsigned u;
    asm volatile("ld.relaxed.gpu.global.u32 %0, [%1];" : "=r"(u) : "l"(p) : "memory");
    return u;
}
__device__ __forceinline__ uint2 ll_load2(const unsigned* p) {
    uint2 v;
    asm volatile("ld.relaxed.gpu.global.v2.u32 {%0,%1}, [%2];" : "=r"(v.x), "=r"(v.y) : "l"(p) : "memory");
    return v;
}
__device__ __forceinline__ uint4 ll_load4(const unsigned* p) {
    uint4 v;
    asm volatile("ld.relaxed.gpu.global.v4.u32 {%0,%1,%2,%3}, [%4];" : "=r"(v.x), "=r"(v.y), "=r"(v.z), "=r"(v.w) : "l"(p) : "memory");
    return v;
}
__device__ __forceinline__ bool ll_ok4(const uint4& v) { return min(min(v.x, v.y), min(v.z, v.w)) != 0u; }
template <int N>
__device__ __forceinline__ void ll_poll4(uint4 (&v)[N], const unsigned* p, int stride, unsigned sleep_ns = 0) {
    unsigned spins = 0;
    while (true) {
        bool ok = true;
#pragma unroll
        for (int k = 0; k < N; k++) v[k] = ll_load4(p + k * stride);
#pragma unroll
        for (int k = 0; k < N; k++) ok = ok && ll_ok4(v[k]);
        if (ok) break;
        if (sleep_ns) __nanosleep(sleep_ns);
        if (++spins > SPIN_LIMIT) __trap();
    }
    __syncwarp();
#pragma unroll
    for (int k = 0; k < N; k++) v[k] = make_uint4(~v[k].x, ~v[k].y, ~v[k].z, ~v[k].w);
}

__device__ __forceinline__ void bump_counter(unsigned* c) {
    asm volatile("red.relaxed.gpu.global.inc.u32 [%0], %1;" ::"l"(c), "r"(4 * SPLIT + 128 - 1) : "memory");
}
__device__ __forceinline__ void signal_counter(unsigned* c) {
    asm volatile("fence.acq_rel.gpu;" ::: "memory");
    bump_counter(c);
}
__device__ __forceinline__ unsigned ld_acquire(const unsigned* c) {
    unsigned v;
    asm volatile("ld.acquire.gpu.global.u32 %0, [%1];" : "=r"(v) : "l"(c) : "memory");
    return v;
}
__device__ __forceinline__ uint32_t pv_mask(int c, int g, int t) {
    return (c == (g ^ (2 * t)) ? 0x0000ffffu : 0u) | (c == (g ^ (2 * t + 1)) ? 0xffff0000u : 0u);
}

struct Producer {
    uint32_t sbase;
    uint32_t wbar, wpar;
    bool pend;
    int lane;
    uint64_t pol;
    uint32_t si_dst, si_gate;
    int si_x, si_y, si_min;
    bool si_box;
    const void* si_src;
    uint64_t si_pol;
    __device__ __forceinline__ uint32_t mb(int i) const { return sbase + OFF_BAR + i * 8; }
    __device__ __forceinline__ void setup_side(const Params& p, int vid) {
        const int cbk = vid >> 1, u = lane & 1;
        si_box = true; si_min = 0; si_gate = mb(MB_X);
        si_pol = lane >= SI_OPART ? policy_evict_normal() : pol;
        int blk = BLK_U + u * 16384;
        if (lane >= SI_OPART) {
            si_box = false; si_src = p.sc->opart + ((cbk >> 1) * SPLIT + 2 * u) * 2048;
            si_gate = mb(MB_CNT);
        } else if (lane >= SI_WE) {
            const int q = lane - SI_WE;
            si_src = &p.tm[5]; blk = BLK_W + q * 16384;
            si_x = 64 * cbk; si_y = 128 * q;
            si_gate = mb(MB_F0); si_min = TUNED(ITE) + TUNED(WESTEP) * q;
        } else {
            si_src = &p.tm[4]; si_x = (vid & 31) * 128 + 64 * u; si_y = 128 * (vid >> 5);
        }
        si_dst = sbase + blk;
    }
    __device__ __forceinline__ bool due(const Params& p, int i, int2 st) const {
        return st.y && (int)(now_ns() - st.y) >= (4 * i - (i < TUNED(IEND) ? TUNED(LEAD) : TUNED(LEADE))) * TUNED(TAU) / 4;
    }
    __device__ __forceinline__ void window(const Params& p, int i, uint32_t bar, uint32_t parity) {
        unsigned busy;
        for (unsigned spins = 0;; spins++) {
            const int2 st = lds_volatile2(sbase + OFF_WIN);
            if (pend) pend = !mbar_test(wbar, wpar);
            busy = __ballot_sync(0xffffffffu, pend);
            const int n = __popc(busy);
            if (__any_sync(0xffffffffu, n < st.x || (n < (i < TUNED(IEND) ? WMAX : TUNED(WMAXE)) && due(p, i, st)))) break;
            if (spins > 16 * SPIN_LIMIT) __trap();
        }
        if (lane == __ffs(~busy) - 1) { wbar = bar; wpar = parity; pend = true; }
    }
    __device__ __forceinline__ void side(const Params& p, int id) {
        const uint32_t bar = mb(MB_SIDE + id);
        if (id < SI_OPART) window(p, 0, bar, 0);
        if (lane == id) {
            mbar_expect_tx(bar, TILE_BYTES);
            if (si_box) {
                tma2d_hint(si_dst, (const CUtensorMap*)si_src, si_x, si_y, bar, si_pol);
            } else {
                asm volatile("fence.proxy.async.global;" ::: "memory");
                bulk_load(si_dst, si_src, TILE_BYTES, bar, si_pol);
            }
        }
        __syncwarp();
    }
    __device__ __forceinline__ void a_tile(const Params& p, int row0, int n) {
        const int st = n % ASTAGES;
        if (lane == 0) mbar_expect_tx(mb(MB_AFULL + st), 32768);
        __syncwarp();
        if (lane < 8) tma2d_hint(sbase + st * 32768 + lane * 4096, &p.tm[6], lane * 64, row0 + n * (32 * SPLIT), mb(MB_AFULL + st), pol);
        __syncwarp();
    }
};

__device__ __forceinline__ void first_load(const Params& p, uint32_t sbase, unsigned blk) {
    const uint32_t bar = sbase + OFF_BAR + MB_FULL * 8;
    mbar_init(bar, 1);
    if (blk % APER != APER - 1) {
        const unsigned c = blk - blk / APER;
        fence_mbar_init();
        mbar_expect_tx(bar, TILE_BYTES);
        bulk_load(sbase + OFF_RING, (const char*)p.K + chunk_off(c), TILE_BYTES, bar, policy_evict_first());
    }
}
__device__ __forceinline__ void next_loads(const Params& p, uint32_t sbase, int vid) {
    const uint32_t bars = sbase + OFF_BAR;
    const uint64_t pol = policy_evict_first();
#pragma unroll
    for (int i = 0; i < MB_EARLY; i++) mbar_init(bars + i * 8, 1);
    fence_mbar_init();
    if (vid >= 0) {
#pragma unroll
        for (int q = 0; q < 4; q++) {
            mbar_expect_tx(bars + (MB_SIDE + q) * 8, TILE_BYTES);
            tma2d_hint(sbase + BLK_W + q * 16384, &p.tm[vid & 1], 64 * (vid >> 1), 128 * q, bars + (MB_SIDE + q) * 8, pol);
            if (q == 0) {
                mbar_expect_tx(bars + MB_X * 8, 4096);
                bulk_load_nohint(sbase + OFF_X, (vid & 1) ? p.xA : p.xB, 4096, bars + MB_X * 8);
            }
        }
    }
}

__device__ __forceinline__ void produce(const Params& p, char* smem, int lane, bool isA, int wk, int vid, int row0) {
    Producer pr;
    pr.sbase = smem_u32(smem);
    pr.lane = lane;
    pr.pol = policy_evict_first();
    pr.pend = !isA && lane < 5;
    pr.wbar = pr.mb(lane == 0 ? MB_FULL : MB_SIDE + lane - 1);
    pr.wpar = 0;
    pr.setup_side(p, vid);
    const int i0 = isA ? 8 * R_JOIN : 0;
    int i = isA ? i0 : 1, i_end = isA ? i0 : I_BOX, s = i - i0, ph = 0;
    int chunk = chunk_of(i >> 3, wk, vid);
    const char* src = (const char*)p.K + chunk_off(chunk) + (i & 3) * CHUNK_STEP;
    int nx = SI_WUK, nx_end = vid < 0 ? 0 : isA || (vid & 1) ? SI_WE : SI_WO;
    uint32_t gate = pr.mb(MB_X);
    int gmin = 0;
    bool last_tile = false;
#pragma unroll 1
    for (int phase = 0; phase < 3; phase++) {
#pragma unroll 1
        while (i < i_end || nx < nx_end) {
            if (nx < nx_end && i >= gmin) {
                bool side = true;
                if (i == i_end) mbar_wait(gate, 0);
                else side = __all_sync(0xffffffffu, mbar_test(gate, 0) &&
                                       (last_tile || (i - i0 >= NS && !mbar_test(pr.mb(MB_EMPTY + s), ph ^ 1))));
                if (side) {
                    last_tile = false;
                    pr.side(p, nx);
                    PROF2(160 + nx);
                    nx++;
                    gate = __shfl_sync(0xffffffffu, pr.si_gate, nx);
                    gmin = __shfl_sync(0xffffffffu, pr.si_min, nx);
                    continue;
                }
            }
            last_tile = true;
            const uint32_t full = pr.mb(MB_FULL + s);
            mbar_wait(pr.mb(MB_EMPTY + s), ph ^ 1);
            if (elect_one()) mbar_expect_tx(full, TILE_BYTES);
            pr.window(p, i, full, ph);
            if (elect_one()) bulk_load(pr.sbase + OFF_RING + s * TILE_BYTES, src, TILE_BYTES, full, pr.pol);
            PROF2(i);
            src += CHUNK_STEP;
            if ((++i & 3) == 0) {
                if ((i & 4) == 0) chunk = chunk_of(i >> 3, wk, vid);
                src = (const char*)((i & 4) ? p.V : p.K) + chunk_off(chunk);
            }
            if (++s == NS) { s = 0; ph ^= 1; }
        }
        if (!isA || phase == 2) break;
        if (phase == 0) {
#pragma unroll 1
            for (int k = -ASTAGES; k < ATILES; k++) {
                if (k == 3 - ASTAGES && vid >= 0) mbar_wait(pr.mb(MB_FU), 0);
                if (k >= 0) bar_sync(BAR_R, 352);
                const int n = k < 0 ? k + ASTAGES : k - 2 + ASTAGES;
                if ((k < 0 || k >= 2) && n < ATILES) { pr.a_tile(p, row0, n); PROF2(32 + n); }
            }
            mbar_wait(pr.mb(MB_F3), 0);
            if (vid >= 0 && !(vid & 1)) nx_end = SI_WO;
        } else {
            for (int k = 0; k < 500 && !__any_sync(0xffffffffu, pr.due(p, i0, lds_volatile2(pr.sbase + OFF_WIN))); k++) __nanosleep(100);
            i_end = vid >= 0 ? I_BOX : 8 * R_LATE;
        }
    }
    if (vid < 0) return;
    mbar_wait(pr.mb((vid & 1) ? MB_F0 : MB_F2), 0);
#pragma unroll 1
    for (int u = 0; u < 4; u++) {
        const uint32_t bar = pr.mb(MB_SIDE + SI_WO + u);
        if (elect_one()) {
            mbar_expect_tx(bar, u < 3 ? TILE_BYTES : TILE_BYTES / 2);
            if (u == 3) mbar_expect_tx(bar + 8, TILE_BYTES / 2);
        }
        pr.window(p, I_BOX + u, bar, 0);
        if (elect_one()) {
#pragma unroll
            for (int k = 0; k < 2; k++)
                tma2d_hint(pr.sbase + BLK_W + u * TILE_BYTES + k * (TILE_BYTES / 2), &p.tm[2 + (vid & 1)], 64 * ((vid >> 1) & 7),
                           1024 * u + 128 * (vid >> 4) + 64 * k, bar + (u == 3 ? 8 * k : 0), pr.pol);
        }
        if (u == TUNED(GO) && elect_one()) mbar_expect_tx(pr.mb(MB_GO), 0);
        PROF2(I_BOX + u);
    }
}

__device__ __forceinline__ void consume(const Params& p, char* smem, bool isA, int wk, int vid, int w, int lane) {
    const uint32_t sbase = smem_u32(smem);
    const uint32_t bars = sbase + OFF_BAR;
    const int g = lane >> 2, t = lane & 3;
    const int mat = lane >> 3, r8 = lane & 7;
    const uint32_t kbase = sbase + OFF_RING + (r8 + 8 * (mat & 1)) * 256 + (mat >> 1) * 128 + r8 * 16;
    const uint32_t vbase = sbase + OFF_RING + (r8 + 8 * (mat >> 1)) * 256 + (mat & 1) * 128 + r8 * 16;
    uint32_t mask[8];
#pragma unroll
    for (int c = 0; c < 8; c++) mask[c] = pv_mask(c, g, t);
    uint32_t* qtab = (uint32_t*)(smem + OFF_Q);
    if (!isA) {
        mbar_wait(bars + MB_F0 * 8, 0);
        __nanosleep(TUNED(QSLEEP));
        const unsigned* src = p.sc->qB + (chunk_of(0, wk, vid) >> 4) * 64 + lane;
        unsigned q0, q1, spins = 0;
        while (true) {
            q0 = ll_load(src);
            q1 = ll_load(src + 32);
            if (q0 && q1) break;
            __nanosleep(200);
            if (++spins > SPIN_LIMIT) __trap();
        }
        qtab[lane] = ~q0;
        qtab[32 + lane] = ~q1;
        __syncwarp();
        if (w == 0) PROF(1);
    }
    const int r_end = vid >= 0 ? R_LATE + 1 : R_LATE;
    int s = w, ph = 0;
    int done = 0;
#pragma unroll 1
    for (int r = isA ? R_JOIN : 0; r < r_end; r++) {
        const int chunk = chunk_of(r, wk, vid);
        if (r >= 1) mbar_wait(bars + MB_Q * 8, 0);
        uint32_t qf[8][2];
#pragma unroll
        for (int c = 0; c < 8; c++) {
            qf[c][0] = qtab[r * 64 + (c ^ g) * 4 + t];
            qf[c][1] = qtab[r * 64 + 32 + (c ^ g) * 4 + t];
        }
        uint32_t pf[2][4][2];
        float m[2], l[2];
#pragma unroll
        for (int u = 0; u < 2; u++) {
            mbar_wait(bars + (MB_FULL + s) * 8, ph);
            done++;
            float acc[4][4];
#pragma unroll
            for (int gr = 0; gr < 4; gr++) zero4(acc[gr]);
#pragma unroll
            for (int c = 0; c < 8; c++) {
#pragma unroll
                for (int gr = 0; gr < 4; gr++) {
                    uint32_t a0, a1, a2, a3;
                    ldsm4(a0, a1, a2, a3, (kbase ^ (c << 4)) + s * TILE_BYTES + gr * 4096);
                    mma(acc[gr], a0, a1, a2, a3, qf[c][0], qf[c][1]);
                }
            }
            warp_release(bars + (MB_EMPTY + s) * 8, lane, (acc[0][0] + acc[1][0]) + (acc[2][0] + acc[3][0]));
#pragma unroll
            for (int gr = 0; gr < 4; gr++) {
                const uint32_t su = score_round2((g & 1) ? acc[gr][1] : acc[gr][0], (g & 1) ? acc[gr][3] : acc[gr][2]);
                const uint32_t x = __shfl_sync(0xffffffffu, su, 9 * t), y = __shfl_sync(0xffffffffu, su, 9 * t + 4);
                pf[u][gr][0] = __byte_perm(x, y, 0x5410);
                pf[u][gr][1] = __byte_perm(x, y, 0x7632);
            }
            m[u] = -INFINITY;
            l[u] = 0.f;
#pragma unroll
            for (int k = 0; k < 8; k++) m[u] = fmaxf(m[u], fmaxf(bf_lo(pf[u][k >> 1][k & 1]), bf_hi(pf[u][k >> 1][k & 1])));
            m[u] = fmaxf(m[u], __shfl_xor_sync(0xffffffffu, m[u], 1));
            m[u] = fmaxf(m[u], __shfl_xor_sync(0xffffffffu, m[u], 2));
#pragma unroll
            for (int k = 0; k < 8; k++) {
                uint32_t& x = pf[u][k >> 1][k & 1];
                const float e0 = ex2((bf_lo(x) - m[u]) * LOG2E), e1 = ex2((bf_hi(x) - m[u]) * LOG2E);
                l[u] += e0 + e1;
                x = pack_bf16(e0, e1);
            }
            l[u] += __shfl_xor_sync(0xffffffffu, l[u], 1);
            l[u] += __shfl_xor_sync(0xffffffffu, l[u], 2);
            if (lane == 0) sts_volatile(sbase + OFF_DONE + 4 * w, done);
            if ((s += 2) >= NS) { s -= NS; ph ^= 1; }
        }
        const float mw = fmaxf(m[0], m[1]);
        float o[4] = {0.f, 0.f, 0.f, 0.f}, lw = 0.f;
#pragma unroll
        for (int u = 0; u < 2; u++) {
            const float a = ex2((m[u] - mw) * LOG2E);
            lw = fmaf(a, l[u], lw);
            float oacc[4][4];
#pragma unroll
            for (int gr = 0; gr < 4; gr++) zero4(oacc[gr]);
            mbar_wait(bars + (MB_FULL + s) * 8, ph);
            PROF(u ? 2 + w : 19 + w);
            done++;
#pragma unroll
            for (int c = 0; c < 8; c++) {
#pragma unroll
                for (int gr = 0; gr < 4; gr++) {
                    uint32_t a0, a1, a2, a3;
                    ldsm4t(a0, a1, a2, a3, (vbase ^ (c << 4)) + s * TILE_BYTES + gr * 4096);
                    mma(oacc[gr], a0, a1, a2, a3, pf[u][gr][0] & mask[c], pf[u][gr][1] & mask[c]);
                }
            }
#pragma unroll
            for (int e = 0; e < 4; e++) o[e] = fmaf(a, (oacc[0][e] + oacc[1][e]) + (oacc[2][e] + oacc[3][e]), o[e]);
            warp_release(bars + (MB_EMPTY + s) * 8, lane, o[0]);
            if (lane == 0) sts_volatile(sbase + OFF_DONE + 4 * w, done);
            if ((s += 2) >= NS) { s -= NS; ph ^= 1; }
        }
        float4* op = (float4*)(smem + OFF_OPART) + (r & 1) * 32 + lane;
        float2* ml = (float2*)(smem + OFF_ML) + (r & 1);
        if (w == 0) {
            *op = make_float4(o[0], o[1], o[2], o[3]);
            if (lane == 0) *ml = make_float2(mw, lw);
            bar_arrive(BAR_B + (r & 1), 64);
        } else {
            bar_sync(BAR_B + (r & 1), 64);
            const float2 ot = *ml;
            const float4 oo = *op;
            const float M = fmaxf(mw, ot.x), a = ex2((mw - M) * LOG2E), b = ex2((ot.x - M) * LOG2E);
            ll_store4(p.sc->part + chunk * 128 + lane * 4, a * o[0] + b * oo.x, a * o[1] + b * oo.y,
                      a * o[2] + b * oo.z, a * o[3] + b * oo.w);
            if (lane == 0) ll_store2(p.sc->pml + chunk * 2, __float_as_uint(M), __float_as_uint(a * lw + b * ot.y));
            PROF(10);
        }
    }
}

__device__ __forceinline__ uint2 merge_chunks(const Params& p, int pair, int lane) {
    Scratch* sc = p.sc;
    const unsigned* pm = sc->pml + pair * 32 + 2 * (lane & 15);
    const unsigned* base = sc->part + pair * 2048 + 4 * lane;
    unsigned um = 0, ul = 0;
    uint4 u[16];
#pragma unroll
    for (int c = 0; c < 16; c++) u[c] = make_uint4(0, 0, 0, 0);
    for (unsigned spins = 0;; spins++) {
        if (!(um && ul)) { um = ll_load(pm); ul = ll_load(pm + 1); }
#pragma unroll
        for (int c = 0; c < 16; c++)
            if (!ll_ok4(u[c])) u[c] = ll_load4(base + c * 128);
        bool ok = um && ul;
#pragma unroll
        for (int c = 0; c < 16; c++) ok &= ll_ok4(u[c]);
        if (__all_sync(0xffffffffu, ok)) break;
        __nanosleep(100);
        if (spins > SPIN_LIMIT) __trap();
    }
    const float m = __uint_as_float(~um);
    const float M = redux_max(m);
    const float wgt = ex2((m - M) * LOG2E);
    float l = wgt * __uint_as_float(~ul);
#pragma unroll
    for (int k = 8; k > 0; k >>= 1) l += __shfl_xor_sync(0xffffffffu, l, k);
    float o[4] = {0.f, 0.f, 0.f, 0.f};
#pragma unroll
    for (int c = 0; c < 16; c++) {
        const float wc = __shfl_sync(0xffffffffu, wgt, c);
        o[0] = fmaf(wc, __uint_as_float(~u[c].x), o[0]); o[1] = fmaf(wc, __uint_as_float(~u[c].y), o[1]);
        o[2] = fmaf(wc, __uint_as_float(~u[c].z), o[2]); o[3] = fmaf(wc, __uint_as_float(~u[c].w), o[3]);
    }
    const float inv = __frcp_rn(l);
    const uint32_t lo = pack_bf16(o[0] * inv, o[2] * inv), hi = pack_bf16(o[1] * inv, o[3] * inv);
    const bool odd = lane & 4;
    const uint32_t x = __shfl_xor_sync(0xffffffffu, odd ? lo : hi, 4), a = odd ? x : lo, b = odd ? hi : x;
    return make_uint2(__byte_perm(a, b, 0x5410), __byte_perm(a, b, 0x7632));
}

__device__ __forceinline__ int qabs_word(int b, int h, int j, int ks, int nt, int t) {
    return b * 8192 + (((h >> 4) + 2 * j) * 8 + ks) * 128 + ((h & 7) * 4 + t) * 4 + ((h >> 3) & 1) + 2 * nt;
}
__device__ __forceinline__ void service(const Params& p, char* smem, bool isA, int vid, int lane) {
    const uint32_t sbase = smem_u32(smem);
    const int i0 = isA ? 8 * R_JOIN : 0, stop = vid >= 0 ? I_BOX : 8 * R_LATE - 4;
    const int c = 16 * vid + 15;
    const int rl = c < R_JOIN * NB ? c / NB : R_JOIN + (c - R_JOIN * NB) / NCTA;
    const int due = 8 * (rl + 1) + (rl + 1 == R_LATE ? TUNED(MERGE) : TUNED(MERGE0));
    const int ow = 8 * (lane & 3) + (lane & 4) + (lane >> 3);
    bool merged = vid < 0 || vid >= N_EARLY, counted = vid < 0;
    int last = i0, z = 0;
    unsigned t0 = clock(), t1 = t0, prev = 0;
    if (isA) mbar_wait(sbase + OFF_BAR + MB_F3 * 8, 0);
    for (unsigned spins = 0; last < stop || !counted || !merged; spins++) {
        const int pos = __shfl_sync(0xffffffffu, i0 + lds_volatile(sbase + OFF_DONE) + lds_volatile(sbase + OFF_DONE + 4), 0);
        if (!merged && pos > due) {
            const int pair = vid;
            const uint2 o = merge_chunks(p, pair, lane);
            ll_store(p.sc->oB + pair * 64 + ow, o.x);
            ll_store(p.sc->oB + pair * 64 + ow + 32, o.y);
#pragma unroll
            for (int k = 0; k < 16; k++) *(uint4*)(p.sc->part + pair * 2048 + k * 128 + 4 * lane) = make_uint4(0, 0, 0, 0);
            p.sc->pml[pair * 32 + lane] = 0;
            *(uint2*)(p.sc->qB + pair * 64 + 2 * lane) = make_uint2(0, 0);
            PROF(12);
            merged = true;
            continue;
        }
        const int cur = min(pos, stop);
        const unsigned now = __shfl_sync(0xffffffffu, (unsigned)clock(), 0);
        const bool look = isA ? now - t1 > 1200 : cur > last;
        unsigned old = 0;
        if (look && lane == 0)
            asm volatile("atom.relaxed.gpu.global.add.u32 %0, [%1], %2;" : "=r"(old) : "l"(&p.sc->prog), "r"(isA ? 0 : cur - last) : "memory");
        if (!counted && now - t0 > 2000 && (isA || pos > TUNED(CNT0))) {
            t0 = now;
            if (__all_sync(0xffffffffu, ld_acquire(&p.sc->cnt) >= 4 * SPLIT)) {
                if (lane == 0) {
                    mbar_expect_tx(sbase + OFF_BAR + MB_CNT * 8, 0);
                    bump_counter(&p.sc->cnt);
                }
                *(uint2*)(p.sc->qA + vid * 64 + lane * 2) = make_uint2(0, 0);
                *(uint4*)(p.sc->qabs + vid * 256 + lane * 4) = make_uint4(0, 0, 0, 0);
                *(uint4*)(p.sc->qabs + vid * 256 + 128 + lane * 4) = make_uint4(0, 0, 0, 0);
                counted = true;
            }
        }
        if (look) {
            if (lane == 0) {
                if (!isA && old + (cur - last) == I_BOX * NB) p.sc->prog = 0;
                if (old > prev && old >= 6 * NB && old < (I_BOX - 2) * NB) {
                    const int zn = clock_after(old) - old * TUNED(TAU) / NB + ((vid >> 4) & 7) * TUNED(STAG);
                    z = prev && zn - z < TUNED(JUMP) ? z + ((zn - z) >> TUNED(GAIN)) : zn;
                    prev = old;
                    sts_volatile2(sbase + OFF_WIN, old < TUNED(IMIN) * NB ? TUNED(WMIN0) : TUNED(WMIN), z);
                }
            }
            t1 = now;
        } else {
            __nanosleep(TUNED(SVC));
        }
        last = cur;
        if (spins > SPIN_LIMIT) __trap();
    }
}

__device__ __forceinline__ void softmax_A(const Params& p, char* smem, int w, int lane, int ab, int asp) {
    const int mat = lane >> 3, r = lane & 7;
    float m_run[4], l_run[4];
#pragma unroll
    for (int i = 0; i < 4; i++) { m_run[i] = -INFINITY; l_run[i] = 0.f; }
    const float* red = (const float*)(smem + OFF_ARED);
    for (int k = 0; k < ATILES; k++) {
        bar_sync(BAR_R, 352);
        float4 s[4];
        float mt[4];
#pragma unroll
        for (int i = 0; i < 4; i++) {
            const float* src = red + (16 * w + 4 * i + mat) * 40 + 4 * r;
            const float4 a = *(const float4*)src, b = *(const float4*)(src + 32 * 40);
            const float4 c = *(const float4*)(src + 64 * 40), d = *(const float4*)(src + 96 * 40);
            const uint32_t v0 = score_round2((a.x + b.x) + (c.x + d.x), (a.y + b.y) + (c.y + d.y));
            const uint32_t v1 = score_round2((a.z + b.z) + (c.z + d.z), (a.w + b.w) + (c.w + d.w));
            s[i] = make_float4(bf_lo(v0), bf_hi(v0), bf_lo(v1), bf_hi(v1));
            mt[i] = fmaxf(fmaxf(s[i].x, s[i].y), fmaxf(s[i].z, s[i].w));
        }
#pragma unroll
        for (int o = 1; o < 8; o <<= 1)
#pragma unroll
            for (int i = 0; i < 4; i++) mt[i] = fmaxf(mt[i], __shfl_xor_sync(0xffffffffu, mt[i], o));
#pragma unroll
        for (int i = 0; i < 4; i++) {
            const int head = 16 * w + 4 * i + mat;
            const float m_new = fmaxf(m_run[i], mt[i]);
            const float al = ex2((m_run[i] - m_new) * LOG2E);
            const float e0 = ex2((s[i].x - m_new) * LOG2E), e1 = ex2((s[i].y - m_new) * LOG2E);
            const float e2 = ex2((s[i].z - m_new) * LOG2E), e3 = ex2((s[i].w - m_new) * LOG2E);
            l_run[i] = l_run[i] * al + (e0 + e1) + (e2 + e3);
            m_run[i] = m_new;
            *(uint2*)(smem + OFF_AP + (k & 1) * 2560 + head * 80 + r * 8) = make_uint2(pack_bf16(e0, e1), pack_bf16(e2, e3));
            if (r == 0) ((float*)(smem + OFF_AALPHA))[(k & 1) * 32 + head] = al;
        }
        bar_arrive(BAR_P, 320);
    }
#pragma unroll
    for (int i = 0; i < 4; i++) {
        float l = l_run[i];
        l += __shfl_xor_sync(0xffffffffu, l, 1);
        l += __shfl_xor_sync(0xffffffffu, l, 2);
        l += __shfl_xor_sync(0xffffffffu, l, 4);
        if (r == 0) p.sc->ml[((16 * w + 4 * i + mat) * SPLIT + asp) * 4 + ab] = make_float2(m_run[i], l);
    }
    bar_arrive(BAR_E, 320);
}

__device__ __forceinline__ void attention_A(const Params& p, char* smem, int sw, int lane, int ab, int asp, bool idle_before) {
    const uint32_t sbase = smem_u32(smem);
    const int tid = sw * 32 + lane;
    const int g = lane >> 2, t = lane & 3, mat = lane >> 3, r = lane & 7;
    const int mi = sw & 1, cq = sw >> 1;
    uint4 qf[8];
    {
        const unsigned* src = p.sc->qabs + ab * 8192 + sw * 1024 + lane * 4;
        for (int k = 0; k < (idle_before ? TUNED(ASLEEP) : TUNED(ASLEEP2)); k++) __nanosleep(1000);
        ll_poll4(qf, src, 128, 500);
        if (sw == 0) PROF(6);
    }
    bar_sync(BAR_S, NSW * 32);
    float oacc[2][8][4];
#pragma unroll
    for (int a = 0; a < 2; a++)
#pragma unroll
        for (int b = 0; b < 8; b++) zero4(oacc[a][b]);
    float* red = (float*)(smem + OFF_ARED) + (cq * 32 + 16 * mi + g) * 40 + 2 * t;
    const uint32_t qk_off = sbase + 2 * cq * 4096 + ((mat >> 1) * 8 + r) * 128 + (((mat & 1) ^ r) << 4);
    const uint32_t pv_off = sbase + sw * 4096 + ((mat & 1) * 8 + r) * 128 + (((mat >> 1) ^ r) << 4);
    const uint32_t p_off = sbase + OFF_AP + ((mat & 1) * 8 + r) * 80 + (mat >> 1) * 16;
    int st = 0, ph = 0, stp = 0;
    for (int k = -1; k < ATILES; k++) {
        float sacc[4][4];
        if (k + 1 < ATILES) {
            mbar_wait(sbase + OFF_BAR + (MB_AFULL + st) * 8, ph);
            if (k == -1 && sw == 0) PROF(13);
#pragma unroll
            for (int a = 0; a < 4; a++) zero4(sacc[a]);
#pragma unroll
            for (int ks = 0; ks < 8; ks++) {
#pragma unroll
                for (int np = 0; np < 2; np++) {
                    uint32_t b0, b1, b2, b3;
                    ldsm4(b0, b1, b2, b3, (qk_off ^ ((ks & 3) << 5)) + st * 32768 + (ks >> 2) * 4096 + np * 2048);
                    mma(sacc[2 * np], qf[ks].x, qf[ks].y, qf[ks].z, qf[ks].w, b0, b1);
                    mma(sacc[2 * np + 1], qf[ks].x, qf[ks].y, qf[ks].z, qf[ks].w, b2, b3);
                }
            }
        }
        if (k >= 0) bar_sync(BAR_P, 320);
        if (k + 1 < ATILES) {
#pragma unroll
            for (int nt = 0; nt < 4; nt++) {
                *(float2*)(red + 8 * nt) = make_float2(sacc[nt][0], sacc[nt][1]);
                *(float2*)(red + 8 * nt + 8 * 40) = make_float2(sacc[nt][2], sacc[nt][3]);
            }
            bar_arrive(BAR_R, 352);
        }
        if (k >= 0) {
            const float* alpha = (const float*)(smem + OFF_AALPHA) + (k & 1) * 32;
            const float al0 = alpha[g], al1 = alpha[g + 8], al2 = alpha[g + 16], al3 = alpha[g + 24];
            if (!__all_sync(0xffffffffu, al0 == 1.f && al1 == 1.f && al2 == 1.f && al3 == 1.f)) {
#pragma unroll
                for (int nt = 0; nt < 8; nt++) {
                    oacc[0][nt][0] *= al0; oacc[0][nt][1] *= al0; oacc[0][nt][2] *= al1; oacc[0][nt][3] *= al1;
                    oacc[1][nt][0] *= al2; oacc[1][nt][1] *= al2; oacc[1][nt][2] *= al3; oacc[1][nt][3] *= al3;
                }
            }
#pragma unroll
            for (int ks = 0; ks < 2; ks++) {
                uint32_t pa[2][4];
#pragma unroll
                for (int mt = 0; mt < 2; mt++)
                    ldsm4(pa[mt][0], pa[mt][1], pa[mt][2], pa[mt][3], p_off + (k & 1) * 2560 + mt * 16 * 80 + ks * 32);
#pragma unroll
                for (int np = 0; np < 4; np++) {
                    uint32_t b0, b1, b2, b3;
                    ldsm4t(b0, b1, b2, b3, (pv_off ^ (np << 5)) + stp * 32768 + ks * 2048);
#pragma unroll
                    for (int mt = 0; mt < 2; mt++) {
                        mma(oacc[mt][2 * np], pa[mt][0], pa[mt][1], pa[mt][2], pa[mt][3], b0, b1);
                        mma(oacc[mt][2 * np + 1], pa[mt][0], pa[mt][1], pa[mt][2], pa[mt][3], b2, b3);
                    }
                }
            }
        }
        stp = st;
        if (++st == ASTAGES) { st = 0; ph ^= 1; }
    }
    if (sw == 0) PROF(14);
    {
        float dep = 0.f;
#pragma unroll
        for (int nt = 0; nt < 8; nt++) dep += oacc[1][nt][0];
        warp_release(sbase + OFF_BAR + MB_F3 * 8, lane, dep);
    }
#pragma unroll
    for (int mt = 0; mt < 2; mt++)
#pragma unroll
        for (int hh = 0; hh < 2; hh++) {
            float4* op = (float4*)(p.sc->opart + ((16 * mt + 8 * hh + g) * SPLIT + asp) * 2048 + sw * 256 + ab * 64) + t;
#pragma unroll
            for (int q = 0; q < 4; q++)
                op[4 * q] = make_float4(oacc[mt][2 * q][2 * hh], oacc[mt][2 * q][2 * hh + 1],
                                    oacc[mt][2 * q + 1][2 * hh], oacc[mt][2 * q + 1][2 * hh + 1]);
        }
    bar_sync(BAR_E, 320);
    if (tid == 0) signal_counter(&p.sc->cnt);
    if (sw == 0) PROF(7);
}

__device__ __forceinline__ float matvec64(char* smem, const uint32_t (&xf)[4][2], int mb_full, int mb_free, int sw, int lane) {
    const uint32_t sbase = smem_u32(smem);
    const int g = lane >> 2, t = lane & 3, mat = lane >> 3, r = lane & 7;
    const uint32_t a = sbase + BLK_W + sw * 8192 + ((mat >> 1) * 8 + r) * 128 + (((mat & 1) ^ r) << 4);
    float c[4][4];
#pragma unroll
    for (int mt = 0; mt < 4; mt++) zero4(c[mt]);
    mbar_wait(sbase + OFF_BAR + (mb_full + (sw >> 1)) * 8, 0);
#pragma unroll
    for (int ks = 0; ks < 4; ks++)
#pragma unroll
        for (int mt = 0; mt < 4; mt++) {
            uint32_t a0, a1, a2, a3;
            ldsm4t(a0, a1, a2, a3, (a ^ (mt << 5)) + ks * 2048);
            mma(c[mt], a0, a1, a2, a3, xf[ks][0], xf[ks][1]);
        }
    warp_release(sbase + OFF_BAR + mb_free * 8, lane, (c[0][0] + c[1][0]) + (c[2][0] + c[3][0]));
    float* rp = (float*)(smem + OFF_RED);
#pragma unroll
    for (int mt = 0; mt < 4; mt++) {
        const float y0 = (t < 2 ? c[mt][0] : c[mt][2]) + __shfl_xor_sync(0xffffffffu, t < 2 ? c[mt][2] : c[mt][0], 2);
        const float y1 = (t < 2 ? c[mt][1] : c[mt][3]) + __shfl_xor_sync(0xffffffffu, t < 2 ? c[mt][3] : c[mt][1], 2);
        float* d = rp + sw * 256 + (t & 1) * 128 + 16 * mt + (t >> 1) * 8 + g;
        d[0] = y0;
        d[64] = y1;
    }
    bar_sync(BAR_S, NSW * 32);
    float y = 0.f;
#pragma unroll
    for (int i = 0; i < NSW; i++) y += rp[i * 256 + sw * 32 + lane];
    return y;
}
__device__ __forceinline__ void load_xfrags(const char* smem, uint32_t (&xf)[4][2], int sw, int lane) {
    const uint32_t* x32 = (const uint32_t*)(smem + OFF_X) + ((lane >> 2) & 3) * 256 + 32 * sw + (lane & 3);
#pragma unroll
    for (int ks = 0; ks < 4; ks++) {
        xf[ks][0] = lane < 16 ? x32[ks * 8] : 0u;
        xf[ks][1] = lane < 16 ? x32[ks * 8 + 4] : 0u;
    }
}
__device__ __forceinline__ int vec_word(int vid, int tid) { return (tid >> 6) * 2048 + (vid >> 1) * 32 + ((tid & 63) >> 1); }
__device__ __forceinline__ void store_vec(unsigned* dst, int vid, int tid, float y) {
    const float y1 = __shfl_down_sync(0xffffffffu, y, 1);
    if (!(tid & 1)) ll_store(dst + vec_word(vid, tid), pack_bf16(y, y1));
}
__device__ __forceinline__ void fill_qtab(const Params& p, char* smem, bool isA, int wk, int vid, int tid) {
    const int r = 1 + (tid >> 4);
    uint4 v[1];
    const bool used = (!isA || r >= R_JOIN) && (vid >= 0 || r < R_LATE);
    const int pair = chunk_of(used ? r : R_JOIN, wk, vid) >> 4;
    ll_poll4(v, p.sc->qB + pair * 64 + (tid & 15) * 4, 0, 300);
    *(uint4*)(smem + OFF_Q + 256 + tid * 16) = v[0];
    __syncwarp();
    if ((tid & 31) == 0) mbar_expect_tx(smem_u32(smem) + OFF_BAR + MB_Q * 8, 0);
}
__device__ __forceinline__ void clear_handoffs(const Params& p, int vid, int tid) {
    const int chunk = chunk_of(R_LATE, 0, vid);
    if (tid < 32) *(uint4*)(p.sc->part + chunk * 128 + tid * 4) = make_uint4(0, 0, 0, 0);
    if (tid == 32) *(uint2*)(p.sc->pml + chunk * 2) = make_uint2(0, 0);
    if ((tid >> 4) == 4 && vid < N_EARLY) *(uint4*)(p.sc->oB + vid * 64 + (tid & 15) * 4) = make_uint4(0, 0, 0, 0);
    if ((tid >> 2) == 24) *(uint4*)(p.out + vid * 32 + (tid & 3) * 8) = make_uint4(0, 0, 0, 0);
    if (!((vid | tid) & 1)) p.sc->ctx[vec_word(vid, tid)] = 0;
}
__device__ __forceinline__ void side_prologue(const Params& p, char* smem, bool isA, int wk, int vid, int sw, int lane) {
    const uint32_t sbase = smem_u32(smem);
    const uint32_t bars = sbase + OFF_BAR;
    const int h = vid & 31, j = vid >> 5;
    const int tid = sw * 32 + lane;
    const int g = lane >> 2, t = lane & 3, mat = lane >> 3, r = lane & 7;
    {
        uint32_t xf[4][2];
        mbar_wait(bars + MB_X * 8, 0);
        load_xfrags(smem, xf, sw, lane);
        if (sw == 0) PROF(16);
        store_vec((vid & 1) ? p.sc->qA : p.sc->qB, vid, tid, matvec64(smem, xf, MB_SIDE + SI_WQ, MB_F0, sw, lane));
        if (sw == 0) PROF(18);
    }
    if (tid == 255) asm volatile("fence.acq_rel.gpu;" ::: "memory");
    __syncwarp();
    __nanosleep(TUNED(GSLEEP));
    if (tid < 64) {
        uint4 v[1];
        ll_poll4(v, p.sc->qA + (tid >> 4) * 2048 + h * 64 + (tid & 15) * 4, 0, 300);
        *(uint4*)(smem + OFF_VEC + (tid >> 4) * 272 + (tid & 15) * 16) = v[0];
    }
    fill_qtab(p, smem, isA, wk, vid, tid);
    bar_sync(BAR_S, NSW * 32);
    if (sw == 0) PROF(21);
    {
        mbar_wait(bars + (MB_SIDE + SI_WUK) * 8, 0);
        mbar_wait(bars + (MB_SIDE + SI_WUK + 1) * 8, 0);
        float c2[2][4];
        zero4(c2[0]); zero4(c2[1]);
        const uint32_t* qa = (const uint32_t*)(smem + OFF_VEC + (g & 3) * 272) + t;
        const uint32_t a = sbase + BLK_U + sw * 2048 + ((mat >> 1) * 8 + r) * 128 + (((mat & 1) ^ r) << 4);
#pragma unroll
        for (int ks = 0; ks < 8; ks++) {
            uint32_t b0, b1, b2, b3;
            ldsm4(b0, b1, b2, b3, (a ^ ((ks & 3) << 5)) + (ks >> 2) * 16384);
            const uint32_t a0 = qa[ks * 8], a2 = qa[ks * 8 + 4];
            mma(c2[0], a0, 0, a2, 0, b0, b1);
            mma(c2[1], a0, 0, a2, 0, b2, b3);
        }
        warp_release(bars + MB_FU * 8, lane, c2[0][0] + c2[1][0]);
        ll_store(p.sc->qabs + qabs_word(g & 3, h, j, sw, g >> 2, t),
                 g < 4 ? pack_bf16(c2[0][0], c2[0][1]) : pack_bf16(c2[1][0], c2[1][1]));
    }
    if (sw == 0) PROF(5);
}

__device__ __forceinline__ void side_epilogue(const Params& p, char* smem, int vid, int sw, int lane) {
    const uint32_t sbase = smem_u32(smem);
    const uint32_t bars = sbase + OFF_BAR;
    const int tid = sw * 32 + lane;
    const int g = lane >> 2, t = lane & 3;
    mbar_wait(bars + MB_CNT * 8, 0);
    if (sw == 0) PROF(8);
    if (vid & 1) {
        for (int k = 0; k < TUNED(CTXSLEEP); k++) __nanosleep(1000);
    } else {
        uint32_t of[4][2];
        const int h = vid >> 2;
        const int b = g & 3, sp = g >> 2;
        float wgt[SPLIT / 2];
        {
            float2 ml[SPLIT / 2];
            float M = -INFINITY, L = 0.f;
#pragma unroll
            for (int q = 0; q < SPLIT / 2; q++) { ml[q] = __ldcg(&p.sc->ml[(h * SPLIT + sp + 2 * q) * 4 + b]); M = fmaxf(M, ml[q].x); }
            M = fmaxf(M, __shfl_xor_sync(0xffffffffu, M, 16));
#pragma unroll
            for (int q = 0; q < SPLIT / 2; q++) { wgt[q] = ex2((ml[q].x - M) * LOG2E); L = fmaf(wgt[q], ml[q].y, L); }
            L += __shfl_xor_sync(0xffffffffu, L, 16);
#pragma unroll
            for (int q = 0; q < SPLIT / 2; q++) { wgt[q] /= L; mbar_wait(bars + (MB_SIDE + SI_OPART + q) * 8, 0); }
        }
#pragma unroll
        for (int ks = 0; ks < 4; ks++) {
            float v[4] = {0.f, 0.f, 0.f, 0.f};
#pragma unroll
            for (int q = 0; q < SPLIT / 2; q++) {
                const float4 u = *((const float4*)(smem + BLK_U) + (sp + 2 * q) * 512 + sw * 64 + b * 16 + 4 * ks + t);
                v[0] = fmaf(u.x, wgt[q], v[0]); v[1] = fmaf(u.y, wgt[q], v[1]);
                v[2] = fmaf(u.z, wgt[q], v[2]); v[3] = fmaf(u.w, wgt[q], v[3]);
            }
#pragma unroll
            for (int e = 0; e < 4; e++) v[e] += __shfl_xor_sync(0xffffffffu, v[e], 16);
#pragma unroll
            for (int hh = 0; hh < 2; hh++) {
                const uint32_t hi = pack_bf16(v[2 * hh], v[2 * hh + 1]);
                of[ks][hh] = sp == 0 ? hi : pack_bf16(v[2 * hh] - bf_lo(hi), v[2 * hh + 1] - bf_hi(hi));
            }
        }
        store_vec(p.sc->ctx, vid, tid, matvec64(smem, of, MB_SIDE + SI_WE, MB_F2, sw, lane));
        if (sw == 0) PROF(9);
    }
    const bool isB = !(vid & 1), late = isB && tid >= 240;
    const unsigned* xs = (isB ? p.sc->oB : p.sc->ctx) + (tid >> 4) * 512 + (vid >> 4) * 64 + (tid & 15) * 4;
    const uint32_t* x32 = (const uint32_t*)(smem + OFF_X) + (g & 3) * XROW + t;
    const uint32_t wa = sbase + BLK_W + lane * 128 + ((sw ^ (lane & 7)) << 4);
    uint32_t* out = (uint32_t*)(p.out + (g & 3) * 1024 + (isB ? 512 : 0) + ((vid >> 1) & 7) * 64 + 8 * sw) + t;
    const unsigned* lp = p.sc->part + late_pair(vid) * 2048 + g * 128 + 16 * sw + 4 * t;
    const unsigned* lm = p.sc->pml + late_pair(vid) * 32 + 2 * g;
    __nv_bfloat16* lx = (__nv_bfloat16*)(smem + OFF_X) + 2 * (3 * XROW + 192) + 16 * t + sw + (lane & 8) + 4 * (lane & 16);
#pragma unroll 1
    for (int pass = 0; pass < 2; pass++) {
        const uint32_t wo = bars + (pass ? MB_SIDE + SI_WO : MB_X) * 8;
        mbar_wait(bars + (pass && isB ? MB_GO : MB_CNT) * 8, 0);
        uint4 v = make_uint4(1, 1, 1, 1);
        for (unsigned spins = 0;; spins++) {
            if (pass && !late) v = ll_load4(xs);
            if (ll_ok4(v)) break;
            __nanosleep(300);
            if (spins > SPIN_LIMIT) __trap();
        }
        __syncwarp();
        if (!late) *(uint4*)(smem + OFF_X + (tid >> 6) * (4 * XROW) + (tid & 63) * 16) = make_uint4(~v.x, ~v.y, ~v.z, ~v.w);
        bar_sync(BAR_S, NSW * 32);
        if (sw == 0) PROF(15);
        float acc[4][4];
#pragma unroll
        for (int k = 0; k < 4; k++) zero4(acc[k]);
        uint4 u0 = make_uint4(1, 1, 1, 1), u1 = u0;
        uint2 m0 = make_uint2(1, 1), m1 = m0;
#pragma unroll
        for (int q = 0; q < 4; q++) {
            if (q == 1 && isB) {
                const int z = lds_volatile(sbase + OFF_WIN + 4) + TUNED(TRIG) * TUNED(TAU) / 4;
                for (int k = pass ? 0 : 63; k < 64 && !__any_sync(0xffffffffu, (int)(now_ns() - z) >= 0); k++) __nanosleep(20);
                if (sw == 0) PROF(27);
                if (pass) { m0 = ll_load2(lm); m1 = ll_load2(lm + 16); u0 = ll_load4(lp); u1 = ll_load4(lp + 1024); }
            }
            if (q == 3) bar_sync(BAR_S, NSW * 32);
            uint32_t xf[16];
#pragma unroll
            for (int k = 0; k < 16; k++) xf[k] = x32[64 * q + 4 * k];
            uint32_t b[4][4];
#pragma unroll
            for (int k = 0; k < 6; k++) {
                if (k == 0 || (q == 3 && k == 2)) mbar_wait(wo + (q + k / 2) * 8, 0);
                if (q == 3 && k == 2 && sw == 0) PROF(11);
                if (k < 4) ldsm4t(b[k][0], b[k][1], b[k][2], b[k][3], wa + q * TILE_BYTES + k * 4096);
                if (k >= 2) {
                    const int j = k - 2;
                    mma(acc[(2 * j) & 3], xf[4 * j], 0, xf[4 * j + 1], 0, b[j][0], b[j][1]);
                    mma(acc[(2 * j + 1) & 3], xf[4 * j + 2], 0, xf[4 * j + 3], 0, b[j][2], b[j][3]);
                }
            }
            if (q == 1 && isB) {
                for (unsigned spins = 0; !__all_sync(0xffffffffu, ll_ok4(u0) && ll_ok4(u1) && ll_ok4(make_uint4(m0.x, m0.y, m1.x, m1.y))); spins++) {
                    if (sw == 0 && spins < 3) PROF2(150 + spins);
                    m0 = ll_load2(lm); m1 = ll_load2(lm + 16); u0 = ll_load4(lp); u1 = ll_load4(lp + 1024);
                    if (spins > SPIN_LIMIT) __trap();
                }
                if (sw == 0) PROF2(153);
                const float a0 = __uint_as_float(~m0.x), a1 = __uint_as_float(~m1.x), M = redux_max(fmaxf(a0, a1));
                const float w0 = ex2((a0 - M) * LOG2E), w1 = ex2((a1 - M) * LOG2E);
                float l = w0 * __uint_as_float(~m0.y) + w1 * __uint_as_float(~m1.y);
                const float o0 = w0 * __uint_as_float(~u0.x) + w1 * __uint_as_float(~u1.x), o1 = w0 * __uint_as_float(~u0.y) + w1 * __uint_as_float(~u1.y);
                const float o2 = w0 * __uint_as_float(~u0.z) + w1 * __uint_as_float(~u1.z), o3 = w0 * __uint_as_float(~u0.w) + w1 * __uint_as_float(~u1.w);
                const bool hi = lane & 16, mid = lane & 8;
                const float e0 = (hi ? o2 : o0) + __shfl_xor_sync(0xffffffffu, hi ? o0 : o2, 16);
                const float e1 = (hi ? o3 : o1) + __shfl_xor_sync(0xffffffffu, hi ? o1 : o3, 16);
                l += __shfl_xor_sync(0xffffffffu, l, 16);
                float e = (mid ? e1 : e0) + __shfl_xor_sync(0xffffffffu, mid ? e0 : e1, 8);
                l += __shfl_xor_sync(0xffffffffu, l, 8);
                e += __shfl_xor_sync(0xffffffffu, e, 4);
                l += __shfl_xor_sync(0xffffffffu, l, 4);
                *lx = __float2bfloat16_rn(__fdividef(e, l));
                if (pass && sw == 0 && !(vid & 15)) *(uint2*)(p.sc->qB + late_pair(vid) * 64 + 2 * lane) = make_uint2(0, 0);
                if (sw == 0) PROF(4);
            }
        }
        const uint32_t y = pack_bf16((acc[0][0] + acc[1][0]) + (acc[2][0] + acc[3][0]), (acc[0][1] + acc[1][1]) + (acc[2][1] + acc[3][1]));
        asm volatile("{\n .reg .pred q;\n setp.ne.u32 q, %2, 0;\n @q red.relaxed.gpu.global.add.noftz.bf16x2 [%0], %1;\n}"
                     ::"l"(out), "r"(y), "r"((int)(pass && lane < 16)) : "memory");
    }
    if (sw == 7) PROF(25);
    if (sw == 2) PROF(24);
}

__global__ void __launch_bounds__(NTHREADS, 1) fused_decode_kernel(const Ptrs ptrs, const __grid_constant__ Maps maps) {
    extern __shared__ __align__(1024) char smem[];
    Params p;
    static_cast<Ptrs&>(p) = ptrs;
    p.tm = maps.tm;
    const unsigned blk = blockIdx.x;
    asm volatile("{\n .reg .u64 a;\n mad.wide.u32 a, %1, 32, %0;\n prefetch.global.L2 [a];\n}" ::"l"(p.K), "r"(blk * NTHREADS + threadIdx.x) : "memory");
    if (threadIdx.x == 0) first_load(p, smem_u32(smem), blk);
    const int warp = __shfl_sync(0xffffffffu, threadIdx.x >> 5, 0), lane = threadIdx.x & 31;
    const bool isA = blk % APER == APER - 1;
    const int aidx = blk / APER, ab = aidx / SPLIT, asp = aidx % SPLIT;
    const int wk = isA ? NB + aidx : blk - aidx;
    const int vid = !isA ? wk : asp == 3 ? -1 : NB + ab * 3 + asp;
    if (threadIdx.x == 32) next_loads(p, smem_u32(smem), vid);
    if (lane == 0 && warp != 1) {
        const int wu = max(warp, 1);
#pragma unroll
        for (int k = 0; k < (MB_COUNT - MB_EARLY + 10) / 11; k++) {
            const int i = MB_EARLY + k * 11 + wu - 1;
            if (i < MB_COUNT && i != MB_FULL) mbar_init(smem_u32(smem) + OFF_BAR + i * 8, i >= MB_F0 ? NSW : 1);
        }
        fence_mbar_init();
        if (wu >= 2 && wu < 7) asm volatile("prefetch.tensormap [%0];" ::"l"(&p.tm[wu]) : "memory");
    }
    __syncwarp();
    if (threadIdx.x == 33) {
        *(int2*)(smem + OFF_DONE) = make_int2(0, 0);
        *(int2*)(smem + OFF_WIN) = make_int2(TUNED(WSTART), 0);
    }
    if (warp >= 4 && vid >= 0) clear_handoffs(p, vid, threadIdx.x - 128);
    bar_sync(0, NTHREADS);
    if (warp == 0) {
        produce(p, smem, lane, isA, wk, vid, ab * 4096 + asp * 32);
    } else if (warp < 3) {
        if (isA) softmax_A(p, smem, warp - 1, lane, ab, asp);
        consume(p, smem, isA, wk, vid, warp - 1, lane);
    } else if (warp == 3) {
        service(p, smem, isA, vid, lane);
    } else {
        const int sw = warp - 4;
        if (vid >= 0) side_prologue(p, smem, isA, wk, vid, sw, lane);
        if (isA) attention_A(p, smem, sw, lane, ab, asp, vid < 0);
        if (vid < 0) fill_qtab(p, smem, isA, wk, vid, threadIdx.x - 128);
        if (vid >= 0) side_epilogue(p, smem, vid, sw, lane);
    }
}

__device__ float g_tmp[2][4 * 32 * 512];
__device__ __forceinline__ float bfr(float x) { return __bfloat162float(__float2bfloat16_rn(x)); }
template <typename X>
__global__ void fb_matvec(const X* x, int xb, int xh, int K, const __nv_bfloat16* W, int wk, int wh, int wn, float* y,
                          __nv_bfloat16* out, bool round) {
    const int n = threadIdx.x, h = blockIdx.x, b = blockIdx.y;
    float s = 0.f;
    for (int k = 0; k < K; k++) s += (float)x[b * xb + h * xh + k] * __bfloat162float(W[(size_t)k * wk + h * wh + (size_t)n * wn]);
    if (out) out[b * 1024 + n] = __float2bfloat16_rn(s);
    else y[(b * gridDim.x + h) * blockDim.x + n] = round ? bfr(s) : s;
}
__global__ void fb_attn(const float* q, const __nv_bfloat16* K, const __nv_bfloat16* V, int D, size_t sb, size_t sh, float* o, bool round) {
    __shared__ float sc[4096], red[8];
    const int h = blockIdx.x, b = blockIdx.y, tid = threadIdx.x;
    K += b * sb + h * sh; V += b * sb + h * sh; q += (b * 32 + h) * D;
    float m = -INFINITY, l = 0.f;
    for (int k = tid; k < 4096; k += 256) {
        float s = 0.f;
        for (int d = 0; d < D; d++) s += q[d] * __bfloat162float(K[(size_t)k * D + d]);
        m = fmaxf(m, sc[k] = bfr(bfr(s) * SCALE));
    }
    m = warp_max(m);
    if (!(tid & 31)) red[tid >> 5] = m;
    __syncthreads();
    for (int i = 0; i < 8; i++) m = fmaxf(m, red[i]);
    __syncthreads();
    for (int k = tid; k < 4096; k += 256) { const float e = expf(sc[k] - m); l += e; sc[k] = bfr(e); }
    l = warp_sum(l);
    if (!(tid & 31)) red[tid >> 5] = l;
    __syncthreads();
    l = 0.f;
    for (int i = 0; i < 8; i++) l += red[i];
    for (int d = tid; d < D; d += 256) {
        float s = 0.f;
        for (int k = 0; k < 4096; k++) s += sc[k] * __bfloat162float(V[(size_t)k * D + d]);
        o[(b * 32 + h) * D + d] = round ? bfr(s / l) : s / l;
    }
}
void launch_fallback(void* const* d_in, __nv_bfloat16* out) {
    typedef const __nv_bfloat16* BP;
    float* t0;
    cudaGetSymbolAddress((void**)&t0, g_tmp);
    float* t1 = t0 + 4 * 32 * 512;
    const dim3 gh(32, 4), g1(1, 4);
    fb_matvec<<<gh, 128>>>((BP)d_in[0], 512, 0, 512, (BP)d_in[2], 4096, 128, 1, t0, nullptr, true);
    fb_matvec<<<gh, 512>>>((const float*)t0, 4096, 128, 128, (BP)d_in[3], 1, 128, 4096, t1, nullptr, true);
    fb_attn<<<gh, 256>>>(t1, (BP)d_in[1], (BP)d_in[1], 512, (size_t)4096 * 512, 0, t0, false);
    fb_matvec<<<gh, 128>>>((const float*)t0, 32 * 512, 512, 512, (BP)d_in[4], 4096, 128, 1, t1, nullptr, true);
    fb_matvec<<<g1, 512>>>((const float*)t1, 4096, 0, 4096, (BP)d_in[5], 512, 0, 1, nullptr, out, false);
    fb_matvec<<<gh, 128>>>((BP)d_in[6], 512, 0, 512, (BP)d_in[9], 4096, 128, 1, t0, nullptr, true);
    fb_attn<<<gh, 256>>>(t0, (BP)d_in[7], (BP)d_in[8], 128, (size_t)32 * 4096 * 128, (size_t)4096 * 128, t1, true);
    fb_matvec<<<g1, 512>>>((const float*)t1, 4096, 0, 4096, (BP)d_in[10], 512, 0, 1, nullptr, out + 512, false);
}

typedef CUresult (*EncodeFn)(CUtensorMap*, CUtensorMapDataType, cuuint32_t, void*, const cuuint64_t*, const cuuint64_t*,
                             const cuuint32_t*, const cuuint32_t*, CUtensorMapInterleave, CUtensorMapSwizzle,
                             CUtensorMapL2promotion, CUtensorMapFloatOOBfill);

void make_map(EncodeFn enc, CUtensorMap* tm, void* ptr, uint64_t cols, uint64_t rows, uint32_t br) {
    const cuuint64_t dims[2] = {cols, rows};
    const cuuint64_t strides[1] = {cols * 2};
    const cuuint32_t box[2] = {64, br};
    const cuuint32_t es[2] = {1, 1};
    enc(tm, CU_TENSOR_MAP_DATA_TYPE_BFLOAT16, 2, ptr, dims, strides, box, es, CU_TENSOR_MAP_INTERLEAVE_NONE,
        CU_TENSOR_MAP_SWIZZLE_128B, CU_TENSOR_MAP_L2_PROMOTION_NONE,
        CU_TENSOR_MAP_FLOAT_OOB_FILL_NONE);
}

}

extern "C" void kernel_launch(void* const* d_in, const int* in_sizes, int n_in, void* d_out, int out_size) {
    (void)in_sizes; (void)n_in; (void)out_size;
    void* fn = nullptr;
    cudaDriverEntryPointQueryResult qr;
    cudaGetDriverEntryPoint("cuTensorMapEncodeTiled", &fn, cudaEnableDefault, &qr);
    EncodeFn enc = (EncodeFn)fn;
    int dev = 0, sms = 0, per_sm = 0;
    cudaGetDevice(&dev);
    cudaDeviceGetAttribute(&sms, cudaDevAttrMultiProcessorCount, dev);
    cudaFuncSetAttribute(fused_decode_kernel, cudaFuncAttributeMaxDynamicSharedMemorySize, SMEM_BYTES);
    cudaOccupancyMaxActiveBlocksPerMultiprocessor(&per_sm, fused_decode_kernel, NTHREADS, SMEM_BYTES);
    if (!enc || sms * per_sm < NCTA) {
        launch_fallback(d_in, (__nv_bfloat16*)d_out);
        return;
    }
    Ptrs p;
    Maps m;
    make_map(enc, &m.tm[0], d_in[9], 4096, 512, 128);
    make_map(enc, &m.tm[1], d_in[2], 4096, 512, 128);
    make_map(enc, &m.tm[2], d_in[10], 512, 4096, 64);
    make_map(enc, &m.tm[3], d_in[5], 512, 4096, 64);
    make_map(enc, &m.tm[4], d_in[3], 4096, 512, 128);
    make_map(enc, &m.tm[5], d_in[4], 4096, 512, 128);
    make_map(enc, &m.tm[6], d_in[1], 512, 4 * 4096, 32);
    p.xA = (const __nv_bfloat16*)d_in[0];
    p.xB = (const __nv_bfloat16*)d_in[6];
    p.K = (const __nv_bfloat16*)d_in[7];
    p.V = (const __nv_bfloat16*)d_in[8];
    p.out = (__nv_bfloat16*)d_out;
    cudaGetSymbolAddress((void**)&p.sc, g_scratch);
    fused_decode_kernel<<<NCTA, NTHREADS, SMEM_BYTES>>>(p, m);
}
```

```cpp
#include <cuda.h>
#include <cuda_runtime.h>
#include <cuda_bf16.h>
#include <stdint.h>

namespace {

#define TV_WSTART 3
#define TV_WMIN0 3
#define TV_WMIN 2
#define TV_IMIN 100
#define TV_LEAD 18
#define TV_LEADE 14
#define TV_WMAXE 3
#define TV_IEND 120
#define TV_TAU 650
#define TV_GAIN 1
#define TV_JUMP 400
#define TV_STAG 80
#define TV_QSLEEP 1600
#define TV_GSLEEP 3000
#define TV_ASLEEP 16
#define TV_ASLEEP2 8
#define TV_ITE 6
#define TV_WESTEP 1
#define TV_CNT0 56
#define TV_MERGE 1
#define TV_MERGE0 6
#define TV_SVC 64
#define TV_GO 2
#define TV_TRIG 541
enum { T_WSTART, T_WMIN0, T_WMIN, T_IMIN, T_LEAD, T_LEADE, T_WMAXE, T_IEND, T_TAU, T_GAIN, T_JUMP, T_STAG, T_QSLEEP, T_GSLEEP, T_ASLEEP, T_ASLEEP2, T_ITE, T_WESTEP, T_CNT0, T_MERGE, T_MERGE0, T_SVC, T_GO, T_TRIG, T_COUNT };
#define TUNED(k) (TV_##k)

constexpr int TK = 64;
constexpr int TILE_BYTES = TK * 256;
constexpr int NS = 6;
constexpr int WMAX = 6;
constexpr int NSW = 8;
constexpr int NTHREADS = (4 + NSW) * 32;
constexpr int SPLIT = 4;
constexpr int AKEYS = 4096 / SPLIT;
constexpr int ATILES = AKEYS / 32;
constexpr int ASTAGES = 6;
constexpr int NCTA = 132;
constexpr int APER = 8;
constexpr int NB = NCTA - 4 * SPLIT;
constexpr int R_JOIN = 12, R_LATE = 16, N_EARLY = 120;
static_assert(R_JOIN * NB + (R_LATE - R_JOIN) * NCTA == N_EARLY * 16, "early chunks");
constexpr int I_LAST = 8 * R_LATE + 4;
static_assert(I_LAST % (2 * NS) == 0 && (8 * R_JOIN) % (2 * NS) == 0, "stage and parity of the last tiles");
constexpr int I_BOX = I_LAST + 4;
__device__ __forceinline__ int late_pair(int vid) { return N_EARLY + (vid >> 4); }
__device__ __forceinline__ int chunk_of(int r, int wk, int vid) {
    return r * NB + max(r - R_JOIN, 0) * (NCTA - NB) + (r == R_LATE ? vid : wk);
}

#define CGRP 16
constexpr int CHUNK_STEP = CGRP * TILE_BYTES;
__device__ __forceinline__ size_t chunk_off(unsigned c) { return (size_t)(4 * c - 3 * (c % CGRP)) * TILE_BYTES; }

constexpr int OFF_RING = 0;
constexpr int OFF_SIDE = NS * TILE_BYTES;
constexpr int OFF_SCR = OFF_SIDE + 98304;
constexpr int OFF_X = OFF_SCR;
constexpr int XROW = 264;
constexpr int OFF_RED = OFF_SCR + 8192;
constexpr int OFF_ARED = OFF_SCR;
constexpr int OFF_AP = OFF_ARED + 4 * 32 * 40 * 4;
constexpr int OFF_AALPHA = OFF_AP + 2 * 32 * 80;
constexpr int OFF_OPART = OFF_AALPHA + 256;
constexpr int OFF_ML = OFF_OPART + 2 * 512;
constexpr int OFF_PH = OFF_ML + 16;
constexpr int OFF_MLO = OFF_PH + 512;
constexpr int OFF_DONE = OFF_MLO + 32;
constexpr int OFF_WIN = OFF_DONE + 8;
constexpr int OFF_VEC = OFF_WIN + 8;
constexpr int OFF_Q = OFF_VEC + 4 * 68 * 4;
constexpr int OFF_BAR = OFF_Q + (R_LATE + 1) * 256;
enum { SI_WQ = 0, SI_WUK = 4, SI_WE = 6, SI_OPART = 10, SI_WO = 12, SI_COUNT = SI_WO + 5 };
enum {
    MB_X = 0, MB_SIDE = 1, MB_EARLY = MB_SIDE + 4,
    MB_FULL = MB_SIDE + SI_COUNT,
    MB_AFULL = MB_FULL + NS,
    MB_CNT = MB_AFULL + ASTAGES,
    MB_PH,
    MB_EMPTY,
    MB_F0 = MB_EMPTY + NS, MB_FU, MB_F2, MB_F3,
    MB_Q,
    MB_COUNT
};
constexpr int SMEM_BYTES = OFF_BAR + MB_COUNT * 8;
static_assert(SMEM_BYTES <= 232448, "smem");
constexpr int BLK_W = OFF_SIDE;
constexpr int BLK_U = OFF_SIDE + 65536;

constexpr int BAR_B = 9  , BAR_S = 2, BAR_R = 5, BAR_P = 6, BAR_E = 7;

constexpr float SCALE = 0.08838834764831845f;
constexpr float LOG2E = 1.4426950408889634f;
constexpr unsigned SPIN_LIMIT = 1u << 22;

struct Scratch {
    float opart[32 * SPLIT * 2048];
    unsigned qB[4 * 2048];
    unsigned qA[4 * 2048];
    unsigned qabs[4 * 8192];
    unsigned ctx[4 * 2048];
    unsigned oB[4 * 2048];
    unsigned part[2048 * 128];
    unsigned pml[2048 * 2];
    float2 ml[32 * SPLIT * 4];
    unsigned prog, pad[31];
    unsigned cnt;
};
__device__ __align__(128) Scratch g_scratch;

struct Ptrs {
    const __nv_bfloat16 *K, *V, *xA, *xB;
    __nv_bfloat16* out;
    Scratch* sc;
};
struct Maps {
    CUtensorMap tm[8];
};
struct Params : Ptrs {
    const CUtensorMap* tm;
};

#define PROF(i)
#define PROF2(i)

__device__ __forceinline__ uint32_t smem_u32(const void* p) { return (uint32_t)__cvta_generic_to_shared(p); }
__device__ __forceinline__ void mbar_init(uint32_t bar, int cnt) {
    asm volatile("mbarrier.init.shared::cta.b64 [%0], %1;" ::"r"(bar), "r"(cnt) : "memory");
}
__device__ __forceinline__ void mbar_expect_tx(uint32_t bar, uint32_t bytes) {
    asm volatile("mbarrier.arrive.expect_tx.shared::cta.b64 _, [%0], %1;" ::"r"(bar), "r"(bytes) : "memory");
}
__device__ __forceinline__ bool mbar_try(uint32_t bar, uint32_t parity) {
    uint32_t ok;
    asm volatile("{\n .reg .pred p;\n mbarrier.try_wait.parity.shared::cta.b64 p, [%1], %2;\n selp.u32 %0, 1, 0, p;\n}"
                 : "=r"(ok) : "r"(bar), "r"(parity) : "memory");
    return ok;
}
__device__ __forceinline__ void mbar_wait(uint32_t bar, uint32_t parity) {
    unsigned spins = 0;
    while (!mbar_try(bar, parity))
        if (++spins > SPIN_LIMIT) __trap();
}
__device__ __forceinline__ void mbar_wait_unless(bool done, uint32_t bar) {
    for (unsigned spins = 0; !done; done = mbar_try(bar, 0))
        if (++spins > SPIN_LIMIT) __trap();
}
__device__ __forceinline__ bool mbar_test(uint32_t bar, uint32_t parity) {
    uint32_t ok;
    asm volatile("{\n .reg .pred p;\n mbarrier.test_wait.parity.shared::cta.b64 p, [%1], %2;\n selp.u32 %0, 1, 0, p;\n}"
                 : "=r"(ok) : "r"(bar), "r"(parity) : "memory");
    return ok;
}
__device__ __forceinline__ void warp_release(uint32_t bar, int lane, float dep) {
    const uint32_t any = __ballot_sync(0xffffffffu, dep != dep);
    if (lane == 0)
        asm volatile("{\n .reg .pred q;\n setp.eq.u32 q, %1, 0;\n @q mbarrier.arrive.shared::cta.b64 _, [%0];\n"
                     " @!q mbarrier.arrive.shared::cta.b64 _, [%0];\n}" ::"r"(bar), "r"(any) : "memory");
}
__device__ __forceinline__ bool elect_one() {
    uint32_t e;
    asm volatile("{\n .reg .pred p;\n elect.sync _|p, 0xffffffff;\n selp.u32 %0, 1, 0, p;\n}" : "=r"(e));
    return e;
}
__device__ __forceinline__ int lds_volatile(uint32_t addr) {
    int v;
    asm volatile("ld.volatile.shared.u32 %0, [%1];" : "=r"(v) : "r"(addr) : "memory");
    return v;
}
__device__ __forceinline__ int2 lds_volatile2(uint32_t addr) {
    int2 v;
    asm volatile("ld.volatile.shared.v2.u32 {%0, %1}, [%2];" : "=r"(v.x), "=r"(v.y) : "r"(addr) : "memory");
    return v;
}
__device__ __forceinline__ void sts_volatile2(uint32_t addr, int a, int b) {
    asm volatile("st.volatile.shared.v2.u32 [%0], {%1, %2};" ::"r"(addr), "r"(a), "r"(b) : "memory");
}
__device__ __forceinline__ void sts_volatile(uint32_t addr, int v) {
    asm volatile("st.volatile.shared.u32 [%0], %1;" ::"r"(addr), "r"(v) : "memory");
}
__device__ __forceinline__ unsigned now_ns() {
    unsigned t;
    asm volatile("mov.u32 %0, %%globaltimer_lo;" : "=r"(t) :: "memory");
    return t;
}
__device__ __forceinline__ int clock_after(unsigned dep) {
    int c;
    asm volatile("{\n .reg .pred q;\n setp.eq.u32 q, %1, 0;\n @q mov.u32 %0, %%globaltimer_lo;\n @!q mov.u32 %0, %%globaltimer_lo;\n}" : "=r"(c) : "r"(dep) : "memory");
    return c;
}
__device__ __forceinline__ void fence_mbar_init() { asm volatile("fence.mbarrier_init.release.cluster;" ::: "memory"); }
__device__ __forceinline__ uint64_t policy_evict_first() {
    uint64_t pol;
    asm volatile("createpolicy.fractional.L2::evict_first.b64 %0, 1.0;" : "=l"(pol));
    return pol;
}
__device__ __forceinline__ uint64_t policy_evict_normal() {
    uint64_t pol;
    asm volatile("createpolicy.fractional.L2::evict_normal.b64 %0, 1.0;" : "=l"(pol));
    return pol;
}
__device__ __forceinline__ void bulk_load(uint32_t dst, const void* src, uint32_t bytes, uint32_t bar, uint64_t pol) {
    asm volatile("cp.async.bulk.shared::cluster.global.mbarrier::complete_tx::bytes.L2::cache_hint [%0], [%1], %2, [%3], %4;"
                 ::"r"(dst), "l"(src), "r"(bytes), "r"(bar), "l"(pol) : "memory");
}
__device__ __forceinline__ void bulk_load_nohint(uint32_t dst, const void* src, uint32_t bytes, uint32_t bar) {
    asm volatile("cp.async.bulk.shared::cluster.global.mbarrier::complete_tx::bytes [%0], [%1], %2, [%3];"
                 ::"r"(dst), "l"(src), "r"(bytes), "r"(bar) : "memory");
}
__device__ __forceinline__ void tma2d_hint(uint32_t dst, const CUtensorMap* tm, int x, int y, uint32_t bar, uint64_t pol) {
    asm volatile("cp.async.bulk.tensor.2d.shared::cluster.global.mbarrier::complete_tx::bytes.L2::cache_hint [%0], [%1, {%3, %4}], [%2], %5;"
                 ::"r"(dst), "l"(tm), "r"(bar), "r"(x), "r"(y), "l"(pol) : "memory");
}
__device__ __forceinline__ void ldsm4(uint32_t& r0, uint32_t& r1, uint32_t& r2, uint32_t& r3, uint32_t addr) {
    asm volatile("ldmatrix.sync.aligned.m8n8.x4.shared.b16 {%0,%1,%2,%3}, [%4];"
                 : "=r"(r0), "=r"(r1), "=r"(r2), "=r"(r3) : "r"(addr) : "memory");
}
__device__ __forceinline__ void ldsm4t(uint32_t& r0, uint32_t& r1, uint32_t& r2, uint32_t& r3, uint32_t addr) {
    asm volatile("ldmatrix.sync.aligned.m8n8.x4.trans.shared.b16 {%0,%1,%2,%3}, [%4];"
                 : "=r"(r0), "=r"(r1), "=r"(r2), "=r"(r3) : "r"(addr) : "memory");
}
__device__ __forceinline__ void mma(float (&c)[4], uint32_t a0, uint32_t a1, uint32_t a2, uint32_t a3, uint32_t b0, uint32_t b1) {
    asm volatile("mma.sync.aligned.m16n8k16.row.col.f32.bf16.bf16.f32 {%0,%1,%2,%3}, {%4,%5,%6,%7}, {%8,%9}, {%0,%1,%2,%3};"
                 : "+f"(c[0]), "+f"(c[1]), "+f"(c[2]), "+f"(c[3])
                 : "r"(a0), "r"(a1), "r"(a2), "r"(a3), "r"(b0), "r"(b1));
}
__device__ __forceinline__ void zero4(float (&c)[4]) { c[0] = c[1] = c[2] = c[3] = 0.f; }
__device__ __forceinline__ void bar_sync(int id, int n) { asm volatile("bar.sync %0, %1;" ::"r"(id), "r"(n) : "memory"); }
__device__ __forceinline__ void bar_arrive(int id, int n) { asm volatile("bar.arrive %0, %1;" ::"r"(id), "r"(n) : "memory"); }
__device__ __forceinline__ float ex2(float x) { float y; asm("ex2.approx.ftz.f32 %0, %1;" : "=f"(y) : "f"(x)); return y; }
__device__ __forceinline__ uint32_t pack_bf16(float lo, float hi) {
    uint32_t r; asm("cvt.rn.bf16x2.f32 %0, %1, %2;" : "=r"(r) : "f"(hi), "f"(lo)); return r;
}
__device__ __forceinline__ float bf_lo(uint32_t u) { return __uint_as_float(u << 16); }
__device__ __forceinline__ float bf_hi(uint32_t u) { return __uint_as_float(u & 0xffff0000u); }
__device__ __forceinline__ uint32_t score_round2(float a, float b) {
    const uint32_t u = pack_bf16(a, b);
    return pack_bf16(bf_lo(u) * SCALE, bf_hi(u) * SCALE);
}
__device__ __forceinline__ float warp_max(float v) {
#pragma unroll
    for (int o = 16; o > 0; o >>= 1) v = fmaxf(v, __shfl_xor_sync(0xffffffffu, v, o));
    return v;
}
__device__ __forceinline__ float redux_max(float v) {
    const int i = __float_as_int(v), m = __reduce_max_sync(0xffffffffu, i ^ ((i >> 31) & 0x7fffffff));
    return __int_as_float(m ^ ((m >> 31) & 0x7fffffff));
}
__device__ __forceinline__ float warp_sum(float v) {
#pragma unroll
    for (int o = 16; o > 0; o >>= 1) v += __shfl_xor_sync(0xffffffffu, v, o);
    return v;
}

__device__ __forceinline__ void ll_store(unsigned* p, unsigned bits) {
    unsigned u = ~bits;
    u = u ? u : 0x80008000u;
    asm volatile("st.relaxed.gpu.global.u32 [%0], %1;" ::"l"(p), "r"(u) : "memory");
}
__device__ __forceinline__ void ll_store2(unsigned* p, unsigned a, unsigned b) {
    unsigned u = ~a, v = ~b;
    u = u ? u : 0x80008000u;
    v = v ? v : 0x80008000u;
    asm volatile("st.relaxed.gpu.global.v2.u32 [%0], {%1, %2};" ::"l"(p), "r"(u), "r"(v) : "memory");
}
__device__ __forceinline__ void ll_store4(unsigned* p, float a, float b, float c, float d) {
    unsigned u[4] = {~__float_as_uint(a), ~__float_as_uint(b), ~__float_as_uint(c), ~__float_as_uint(d)};
#pragma unroll
    for (int k = 0; k < 4; k++) u[k] = u[k] ? u[k] : 0x80008000u;
    asm volatile("st.relaxed.gpu.global.v4.u32 [%0], {%1, %2, %3, %4};" ::"l"(p), "r"(u[0]), "r"(u[1]), "r"(u[2]), "r"(u[3]) : "memory");
}
__device__ __forceinline__ unsigned ll_load(const unsigned* p) {
    unsigned u;
    asm volatile("ld.relaxed.gpu.global.u32 %0, [%1];" : "=r"(u) : "l"(p) : "memory");
    return u;
}
__device__ __forceinline__ uint2 ll_load2(const unsigned* p) {
    uint2 v;
    asm volatile("ld.relaxed.gpu.global.v2.u32 {%0,%1}, [%2];" : "=r"(v.x), "=r"(v.y) : "l"(p) : "memory");
    return v;
}
__device__ __forceinline__ uint4 ll_load4(const unsigned* p) {
    uint4 v;
    asm volatile("ld.relaxed.gpu.global.v4.u32 {%0,%1,%2,%3}, [%4];" : "=r"(v.x), "=r"(v.y), "=r"(v.z), "=r"(v.w) : "l"(p) : "memory");
    return v;
}
__device__ __forceinline__ bool ll_ok4(const uint4& v) { return min(min(v.x, v.y), min(v.z, v.w)) != 0u; }
template <int N>
__device__ __forceinline__ void ll_poll4(uint4 (&v)[N], const unsigned* p, int stride, unsigned sleep_ns = 0) {
    unsigned spins = 0;
    while (true) {
        bool ok = true;
#pragma unroll
        for (int k = 0; k < N; k++) v[k] = ll_load4(p + k * stride);
#pragma unroll
        for (int k = 0; k < N; k++) ok = ok && ll_ok4(v[k]);
        if (ok) break;
        if (sleep_ns) __nanosleep(sleep_ns);
        if (++spins > SPIN_LIMIT) __trap();
    }
    __syncwarp();
#pragma unroll
    for (int k = 0; k < N; k++) v[k] = make_uint4(~v[k].x, ~v[k].y, ~v[k].z, ~v[k].w);
}

__device__ __forceinline__ void bump_counter(unsigned* c) {
    asm volatile("red.relaxed.gpu.global.inc.u32 [%0], %1;" ::"l"(c), "r"(4 * SPLIT + 128 - 1) : "memory");
}
__device__ __forceinline__ void signal_counter(unsigned* c) {
    asm volatile("fence.acq_rel.gpu;" ::: "memory");
    bump_counter(c);
}
__device__ __forceinline__ unsigned ld_acquire(const unsigned* c) {
    unsigned v;
    asm volatile("ld.acquire.gpu.global.u32 %0, [%1];" : "=r"(v) : "l"(c) : "memory");
    return v;
}
__device__ __forceinline__ uint32_t pv_mask(int c, int g, int t) {
    return (c == (g ^ (2 * t)) ? 0x0000ffffu : 0u) | (c == (g ^ (2 * t + 1)) ? 0xffff0000u : 0u);
}

struct Producer {
    uint32_t sbase;
    uint32_t wbar, wpar;
    bool pend;
    int lane;
    uint64_t pol;
    uint32_t si_dst, si_gate;
    int si_x, si_y, si_min;
    bool si_box;
    const void* si_src;
    uint64_t si_pol;
    __device__ __forceinline__ uint32_t mb(int i) const { return sbase + OFF_BAR + i * 8; }
    __device__ __forceinline__ void setup_side(const Params& p, int vid) {
        const int cbk = vid >> 1, u = lane & 1;
        si_box = true; si_min = 0; si_gate = mb(MB_X);
        si_pol = lane >= SI_OPART ? policy_evict_normal() : pol;
        int blk = BLK_U + u * 16384;
        if (lane >= SI_OPART) {
            si_box = false; si_src = p.sc->opart + ((cbk >> 1) * SPLIT + 2 * u) * 2048;
            si_gate = mb(MB_CNT);
        } else if (lane >= SI_WE) {
            const int q = lane - SI_WE;
            si_src = &p.tm[5]; blk = BLK_W + q * 16384;
            si_x = 64 * cbk; si_y = 128 * q;
            si_gate = mb(MB_F0); si_min = TUNED(ITE) + TUNED(WESTEP) * q;
        } else {
            si_src = &p.tm[4]; si_x = (vid & 31) * 128 + 64 * u; si_y = 128 * (vid >> 5);
        }
        si_dst = sbase + blk;
    }
    __device__ __forceinline__ bool due(const Params& p, int i, int2 st) const {
        return st.y && (int)(now_ns() - st.y) >= (4 * i - (i < TUNED(IEND) ? TUNED(LEAD) : TUNED(LEADE))) * TUNED(TAU) / 4;
    }
    __device__ __forceinline__ void window(const Params& p, int i, uint32_t bar, uint32_t parity) {
        unsigned busy;
        for (unsigned spins = 0;; spins++) {
            const int2 st = lds_volatile2(sbase + OFF_WIN);
            if (pend) pend = !mbar_test(wbar, wpar);
            busy = __ballot_sync(0xffffffffu, pend);
            const int n = __popc(busy);
            if (__any_sync(0xffffffffu, n < st.x || (n < (i < TUNED(IEND) ? WMAX : TUNED(WMAXE)) && due(p, i, st)))) break;
            if (spins > 16 * SPIN_LIMIT) __trap();
        }
        if (lane == __ffs(~busy) - 1) { wbar = bar; wpar = parity; pend = true; }
    }
    __device__ __forceinline__ void side(const Params& p, int id) {
        const uint32_t bar = mb(MB_SIDE + id);
        if (id < SI_OPART) window(p, 0, bar, 0);
        if (lane == id) {
            mbar_expect_tx(bar, TILE_BYTES);
            if (si_box) {
                tma2d_hint(si_dst, (const CUtensorMap*)si_src, si_x, si_y, bar, si_pol);
            } else {
                asm volatile("fence.proxy.async.global;" ::: "memory");
                bulk_load(si_dst, si_src, TILE_BYTES, bar, si_pol);
            }
        }
        __syncwarp();
    }
    __device__ __forceinline__ void a_tile(const Params& p, int row0, int n) {
        const int st = n % ASTAGES;
        if (lane == 0) mbar_expect_tx(mb(MB_AFULL + st), 32768);
        __syncwarp();
        if (lane < 8) tma2d_hint(sbase + st * 32768 + lane * 4096, &p.tm[6], lane * 64, row0 + n * (32 * SPLIT), mb(MB_AFULL + st), pol);
        __syncwarp();
    }
};

__device__ __forceinline__ void first_load(const Params& p, uint32_t sbase, unsigned blk) {
    const uint32_t bar = sbase + OFF_BAR + MB_FULL * 8;
    mbar_init(bar, 1);
    if (blk % APER != APER - 1) {
        const unsigned c = blk - blk / APER;
        fence_mbar_init();
        mbar_expect_tx(bar, TILE_BYTES);
        bulk_load(sbase + OFF_RING, (const char*)p.K + chunk_off(c), TILE_BYTES, bar, policy_evict_first());
    }
}
__device__ __forceinline__ void next_loads(const Params& p, uint32_t sbase, int vid) {
    const uint32_t bars = sbase + OFF_BAR;
    const uint64_t pol = policy_evict_first();
#pragma unroll
    for (int i = 0; i < MB_EARLY; i++) mbar_init(bars + i * 8, 1);
    fence_mbar_init();
    if (vid >= 0) {
#pragma unroll
        for (int q = 0; q < 4; q++) {
            mbar_expect_tx(bars + (MB_SIDE + q) * 8, TILE_BYTES);
            tma2d_hint(sbase + BLK_W + q * 16384, &p.tm[vid & 1], 64 * (vid >> 1), 128 * q, bars + (MB_SIDE + q) * 8, pol);
            if (q == 0) {
                mbar_expect_tx(bars + MB_X * 8, 4096);
                bulk_load_nohint(sbase + OFF_X, (vid & 1) ? p.xA : p.xB, 4096, bars + MB_X * 8);
            }
        }
    }
}

__device__ __forceinline__ void produce(const Params& p, char* smem, int lane, bool isA, int wk, int vid, int row0) {
    Producer pr;
    pr.sbase = smem_u32(smem);
    pr.lane = lane;
    pr.pol = policy_evict_first();
    pr.pend = !isA && lane < 5;
    pr.wbar = pr.mb(lane == 0 ? MB_FULL : MB_SIDE + lane - 1);
    pr.wpar = 0;
    pr.setup_side(p, vid);
    const int i0 = isA ? 8 * R_JOIN : 0;
    int i = isA ? i0 : 1, i_end = isA ? i0 : I_LAST, s = i - i0, ph = 0;
    int chunk = chunk_of(i >> 3, wk, vid);
    const char* src = (const char*)p.K + chunk_off(chunk) + (i & 3) * CHUNK_STEP;
    int nx = SI_WUK, nx_end = vid < 0 ? 0 : isA || (vid & 1) ? SI_WE : SI_WO;
    uint32_t gate = pr.mb(MB_X);
    int gmin = 0;
    bool last_tile = false;
#pragma unroll 1
    for (int phase = 0; phase < 3; phase++) {
#pragma unroll 1
        while (i < i_end || nx < nx_end) {
            if (nx < nx_end && i >= gmin) {
                bool side = true;
                if (i == i_end) mbar_wait(gate, 0);
                else side = __all_sync(0xffffffffu, mbar_test(gate, 0) &&
                                       (last_tile || (i - i0 >= NS && !mbar_test(pr.mb(MB_EMPTY + s), ph ^ 1))));
                if (side) {
                    last_tile = false;
                    pr.side(p, nx);
                    PROF2(160 + nx);
                    nx++;
                    gate = __shfl_sync(0xffffffffu, pr.si_gate, nx);
                    gmin = __shfl_sync(0xffffffffu, pr.si_min, nx);
                    continue;
                }
            }
            last_tile = true;
            const uint32_t full = pr.mb(MB_FULL + s);
            mbar_wait(pr.mb(MB_EMPTY + s), ph ^ 1);
            if (elect_one()) mbar_expect_tx(full, TILE_BYTES);
            pr.window(p, i, full, ph);
            if (elect_one()) bulk_load(pr.sbase + OFF_RING + s * TILE_BYTES, src, TILE_BYTES, full, pr.pol);
            PROF2(i);
            src += CHUNK_STEP;
            if ((++i & 3) == 0) {
                if ((i & 4) == 0) chunk = chunk_of(i >> 3, wk, vid);
                src = (const char*)((i & 4) ? p.V : p.K) + chunk_off(chunk);
            }
            if (++s == NS) { s = 0; ph ^= 1; }
        }
        if (!isA || phase == 2) break;
        if (phase == 0) {
#pragma unroll 1
            for (int k = -ASTAGES; k < ATILES; k++) {
                if (k == 3 - ASTAGES && vid >= 0) mbar_wait(pr.mb(MB_FU), 0);
                if (k >= 0) bar_sync(BAR_R, 352);
                const int n = k < 0 ? k + ASTAGES : k - 2 + ASTAGES;
                if ((k < 0 || k >= 2) && n < ATILES) { pr.a_tile(p, row0, n); PROF2(32 + n); }
            }
            mbar_wait(pr.mb(MB_F3), 0);
            if (vid >= 0 && !(vid & 1)) nx_end = SI_WO;
        } else {
            for (int k = 0; k < 500 && !__any_sync(0xffffffffu, pr.due(p, i0, lds_volatile2(pr.sbase + OFF_WIN))); k++) __nanosleep(100);
            i_end = vid >= 0 ? I_LAST : 8 * R_LATE;
        }
    }
    if (vid < 0) return;
#pragma unroll 1
    for (int u = 0; u < 4; u++) {
        const uint32_t full = pr.mb(MB_FULL + u);
        mbar_wait(pr.mb(MB_EMPTY + u), 1);
        if (elect_one()) mbar_expect_tx(full, TILE_BYTES);
        pr.window(p, I_LAST + u, full, 0);
        if (elect_one()) {
#pragma unroll
            for (int hf = 0; hf < 2; hf++)
                tma2d_hint(pr.sbase + OFF_RING + u * TILE_BYTES + hf * 8192, &p.tm[7], 64 * hf, (chunk_off(chunk) + u * CHUNK_STEP) / 256,
                           full, pr.pol);
        }
        PROF2(I_LAST + u);
    }
    mbar_wait(pr.mb((vid & 1) ? MB_F0 : MB_F2), 0);
#pragma unroll 1
    for (int u = 0; u < 4; u++) {
        const uint32_t bar = pr.mb(MB_SIDE + SI_WO + u);
        if (elect_one()) {
            mbar_expect_tx(bar, u < 3 ? TILE_BYTES : TILE_BYTES / 2);
            if (u == 3) mbar_expect_tx(bar + 8, TILE_BYTES / 2);
        }
        pr.window(p, I_BOX + u, bar, 0);
        if (elect_one()) {
#pragma unroll
            for (int k = 0; k < 2; k++)
                tma2d_hint(pr.sbase + BLK_W + u * TILE_BYTES + k * (TILE_BYTES / 2), &p.tm[2 + (vid & 1)], 64 * ((vid >> 1) & 7),
                           1024 * u + 128 * (vid >> 4) + 64 * k, bar + (u == 3 ? 8 * k : 0), pr.pol);
        }
        PROF2(I_BOX + u);
    }
}

__device__ __forceinline__ void consume(const Params& p, char* smem, bool isA, int wk, int vid, int w, int lane) {
    const uint32_t sbase = smem_u32(smem);
    const uint32_t bars = sbase + OFF_BAR;
    const int g = lane >> 2, t = lane & 3;
    const int mat = lane >> 3, r8 = lane & 7;
    const uint32_t kbase = sbase + OFF_RING + (r8 + 8 * (mat & 1)) * 256 + (mat >> 1) * 128 + r8 * 16;
    const uint32_t vbase = sbase + OFF_RING + (r8 + 8 * (mat >> 1)) * 256 + (mat & 1) * 128 + r8 * 16;
    uint32_t mask[8];
#pragma unroll
    for (int c = 0; c < 8; c++) mask[c] = pv_mask(c, g, t);
    uint32_t* qtab = (uint32_t*)(smem + OFF_Q);
    if (!isA) {
        mbar_wait(bars + MB_F0 * 8, 0);
        __nanosleep(TUNED(QSLEEP));
        const unsigned* src = p.sc->qB + (chunk_of(0, wk, vid) >> 4) * 64 + lane;
        unsigned q0, q1, spins = 0;
        while (true) {
            q0 = ll_load(src);
            q1 = ll_load(src + 32);
            if (q0 && q1) break;
            __nanosleep(200);
            if (++spins > SPIN_LIMIT) __trap();
        }
        qtab[lane] = ~q0;
        qtab[32 + lane] = ~q1;
        __syncwarp();
        if (w == 0) PROF(1);
    }
    const int r_end = vid >= 0 ? R_LATE + 1 : R_LATE;
    int s = w, ph = 0;
    int done = 0;
#pragma unroll 1
    for (int r = isA ? R_JOIN : 0; r < r_end; r++) {
        const int chunk = chunk_of(r, wk, vid);
        if (r >= 1) mbar_wait(bars + MB_Q * 8, 0);
        uint32_t qf[8][2];
#pragma unroll
        for (int c = 0; c < 8; c++) {
            qf[c][0] = qtab[r * 64 + (c ^ g) * 4 + t];
            qf[c][1] = qtab[r * 64 + 32 + (c ^ g) * 4 + t];
        }
        uint32_t pf[2][4][2];
        float m[2], l[2];
#pragma unroll
        for (int u = 0; u < 2; u++) {
            mbar_wait(bars + (MB_FULL + s) * 8, ph);
            done++;
            float acc[4][4];
#pragma unroll
            for (int gr = 0; gr < 4; gr++) zero4(acc[gr]);
#pragma unroll
            for (int c = 0; c < 8; c++) {
#pragma unroll
                for (int gr = 0; gr < 4; gr++) {
                    uint32_t a0, a1, a2, a3;
                    ldsm4(a0, a1, a2, a3, (kbase ^ (c << 4)) + s * TILE_BYTES + gr * 4096);
                    mma(acc[gr], a0, a1, a2, a3, qf[c][0], qf[c][1]);
                }
            }
            warp_release(bars + (MB_EMPTY + s) * 8, lane, (acc[0][0] + acc[1][0]) + (acc[2][0] + acc[3][0]));
#pragma unroll
            for (int gr = 0; gr < 4; gr++) {
                const uint32_t su = score_round2((g & 1) ? acc[gr][1] : acc[gr][0], (g & 1) ? acc[gr][3] : acc[gr][2]);
                const uint32_t x = __shfl_sync(0xffffffffu, su, 9 * t), y = __shfl_sync(0xffffffffu, su, 9 * t + 4);
                pf[u][gr][0] = __byte_perm(x, y, 0x5410);
                pf[u][gr][1] = __byte_perm(x, y, 0x7632);
            }
            m[u] = -INFINITY;
            l[u] = 0.f;
#pragma unroll
            for (int k = 0; k < 8; k++) m[u] = fmaxf(m[u], fmaxf(bf_lo(pf[u][k >> 1][k & 1]), bf_hi(pf[u][k >> 1][k & 1])));
            m[u] = fmaxf(m[u], __shfl_xor_sync(0xffffffffu, m[u], 1));
            m[u] = fmaxf(m[u], __shfl_xor_sync(0xffffffffu, m[u], 2));
#pragma unroll
            for (int k = 0; k < 8; k++) {
                uint32_t& x = pf[u][k >> 1][k & 1];
                const float e0 = ex2((bf_lo(x) - m[u]) * LOG2E), e1 = ex2((bf_hi(x) - m[u]) * LOG2E);
                l[u] += e0 + e1;
                x = pack_bf16(e0, e1);
            }
            l[u] += __shfl_xor_sync(0xffffffffu, l[u], 1);
            l[u] += __shfl_xor_sync(0xffffffffu, l[u], 2);
            if (lane == 0) sts_volatile(sbase + OFF_DONE + 4 * w, done);
            if (r == R_LATE) {
                if (lane < 4) {
                    uint4* dst = (uint4*)(smem + OFF_PH + (2 * u + w) * 128 + t * 32);
                    dst[0] = make_uint4(pf[u][0][0], pf[u][0][1], pf[u][1][0], pf[u][1][1]);
                    dst[1] = make_uint4(pf[u][2][0], pf[u][2][1], pf[u][3][0], pf[u][3][1]);
                    if (lane == 0) ((float2*)(smem + OFF_MLO))[2 * u + w] = make_float2(m[u], l[u]);
                }
                __syncwarp();
                if (lane == 0) mbar_expect_tx(bars + MB_PH * 8, 0);
            }
            if ((s += 2) >= NS) { s -= NS; ph ^= 1; }
        }
        if (r == R_LATE) break;
        const float mw = fmaxf(m[0], m[1]);
        float o[4] = {0.f, 0.f, 0.f, 0.f}, lw = 0.f;
#pragma unroll
        for (int u = 0; u < 2; u++) {
            const float a = ex2((m[u] - mw) * LOG2E);
            lw = fmaf(a, l[u], lw);
            float oacc[4][4];
#pragma unroll
            for (int gr = 0; gr < 4; gr++) zero4(oacc[gr]);
            mbar_wait(bars + (MB_FULL + s) * 8, ph);
            PROF(u ? 2 + w : 19 + w);
            done++;
#pragma unroll
            for (int c = 0; c < 8; c++) {
#pragma unroll
                for (int gr = 0; gr < 4; gr++) {
                    uint32_t a0, a1, a2, a3;
                    ldsm4t(a0, a1, a2, a3, (vbase ^ (c << 4)) + s * TILE_BYTES + gr * 4096);
                    mma(oacc[gr], a0, a1, a2, a3, pf[u][gr][0] & mask[c], pf[u][gr][1] & mask[c]);
                }
            }
#pragma unroll
            for (int e = 0; e < 4; e++) o[e] = fmaf(a, (oacc[0][e] + oacc[1][e]) + (oacc[2][e] + oacc[3][e]), o[e]);
            warp_release(bars + (MB_EMPTY + s) * 8, lane, o[0]);
            if (lane == 0) sts_volatile(sbase + OFF_DONE + 4 * w, done);
            if ((s += 2) >= NS) { s -= NS; ph ^= 1; }
        }
        float4* op = (float4*)(smem + OFF_OPART) + (r & 1) * 32 + lane;
        float2* ml = (float2*)(smem + OFF_ML) + (r & 1);
        if (w == 0) {
            *op = make_float4(o[0], o[1], o[2], o[3]);
            if (lane == 0) *ml = make_float2(mw, lw);
            bar_arrive(BAR_B + (r & 1), 64);
        } else {
            bar_sync(BAR_B + (r & 1), 64);
            const float2 ot = *ml;
            const float4 oo = *op;
            const float M = fmaxf(mw, ot.x), a = ex2((mw - M) * LOG2E), b = ex2((ot.x - M) * LOG2E);
            ll_store4(p.sc->part + chunk * 128 + lane * 4, a * o[0] + b * oo.x, a * o[1] + b * oo.y,
                      a * o[2] + b * oo.z, a * o[3] + b * oo.w);
            if (lane == 0) ll_store2(p.sc->pml + chunk * 2, __float_as_uint(M), __float_as_uint(a * lw + b * ot.y));
            PROF(10);
        }
    }
}

__device__ __forceinline__ uint2 merge_chunks(const Params& p, int pair, int lane) {
    Scratch* sc = p.sc;
    const unsigned* pm = sc->pml + pair * 32 + 2 * (lane & 15);
    const unsigned* base = sc->part + pair * 2048 + 4 * lane;
    unsigned um = 0, ul = 0;
    uint4 u[16];
#pragma unroll
    for (int c = 0; c < 16; c++) u[c] = make_uint4(0, 0, 0, 0);
    for (unsigned spins = 0;; spins++) {
        if (!(um && ul)) { um = ll_load(pm); ul = ll_load(pm + 1); }
#pragma unroll
        for (int c = 0; c < 16; c++)
            if (!ll_ok4(u[c])) u[c] = ll_load4(base + c * 128);
        bool ok = um && ul;
#pragma unroll
        for (int c = 0; c < 16; c++) ok &= ll_ok4(u[c]);
        if (__all_sync(0xffffffffu, ok)) break;
        __nanosleep(100);
        if (spins > SPIN_LIMIT) __trap();
    }
    const float m = __uint_as_float(~um);
    const float M = redux_max(m);
    const float wgt = ex2((m - M) * LOG2E);
    float l = wgt * __uint_as_float(~ul);
#pragma unroll
    for (int k = 8; k > 0; k >>= 1) l += __shfl_xor_sync(0xffffffffu, l, k);
    float o[4] = {0.f, 0.f, 0.f, 0.f};
#pragma unroll
    for (int c = 0; c < 16; c++) {
        const float wc = __shfl_sync(0xffffffffu, wgt, c);
        o[0] = fmaf(wc, __uint_as_float(~u[c].x), o[0]); o[1] = fmaf(wc, __uint_as_float(~u[c].y), o[1]);
        o[2] = fmaf(wc, __uint_as_float(~u[c].z), o[2]); o[3] = fmaf(wc, __uint_as_float(~u[c].w), o[3]);
    }
    const float inv = __frcp_rn(l);
    const uint32_t lo = pack_bf16(o[0] * inv, o[2] * inv), hi = pack_bf16(o[1] * inv, o[3] * inv);
    const bool odd = lane & 4;
    const uint32_t x = __shfl_xor_sync(0xffffffffu, odd ? lo : hi, 4), a = odd ? x : lo, b = odd ? hi : x;
    return make_uint2(__byte_perm(a, b, 0x5410), __byte_perm(a, b, 0x7632));
}

__device__ __forceinline__ int qabs_word(int b, int h, int j, int ks, int nt, int t) {
    return b * 8192 + (((h >> 4) + 2 * j) * 8 + ks) * 128 + ((h & 7) * 4 + t) * 4 + ((h >> 3) & 1) + 2 * nt;
}
__device__ __forceinline__ void service(const Params& p, char* smem, bool isA, int vid, int lane) {
    const uint32_t sbase = smem_u32(smem);
    const int i0 = isA ? 8 * R_JOIN : 0, stop = vid >= 0 ? I_BOX : 8 * R_LATE - 4;
    const int c = 16 * vid + 15;
    const int rl = c < R_JOIN * NB ? c / NB : R_JOIN + (c - R_JOIN * NB) / NCTA;
    const int due = 8 * (rl + 1) + (rl + 1 == R_LATE ? TUNED(MERGE) : TUNED(MERGE0));
    const int ow = 8 * (lane & 3) + (lane & 4) + (lane >> 3);
    bool merged = vid < 0 || vid >= N_EARLY, counted = vid < 0;
    int last = i0, z = 0;
    unsigned t0 = clock(), t1 = t0, prev = 0;
    if (isA) mbar_wait(sbase + OFF_BAR + MB_F3 * 8, 0);
    for (unsigned spins = 0; last < stop || !counted || !merged; spins++) {
        const int pos = __shfl_sync(0xffffffffu, i0 + lds_volatile(sbase + OFF_DONE) + lds_volatile(sbase + OFF_DONE + 4), 0);
        if (!merged && pos > due) {
            const int pair = vid;
            const uint2 o = merge_chunks(p, pair, lane);
            ll_store(p.sc->oB + pair * 64 + ow, o.x);
            ll_store(p.sc->oB + pair * 64 + ow + 32, o.y);
#pragma unroll
            for (int k = 0; k < 16; k++) *(uint4*)(p.sc->part + pair * 2048 + k * 128 + 4 * lane) = make_uint4(0, 0, 0, 0);
            p.sc->pml[pair * 32 + lane] = 0;
            *(uint2*)(p.sc->qB + pair * 64 + 2 * lane) = make_uint2(0, 0);
            PROF(12);
            merged = true;
            continue;
        }
        const int cur = min(pos, stop);
        const unsigned now = __shfl_sync(0xffffffffu, (unsigned)clock(), 0);
        const bool look = isA ? now - t1 > 1200 : cur > last;
        unsigned old = 0;
        if (look && lane == 0)
            asm volatile("atom.relaxed.gpu.global.add.u32 %0, [%1], %2;" : "=r"(old) : "l"(&p.sc->prog), "r"(isA ? 0 : cur - last) : "memory");
        if (!counted && now - t0 > 2000 && (isA || pos > TUNED(CNT0))) {
            t0 = now;
            if (__all_sync(0xffffffffu, ld_acquire(&p.sc->cnt) >= 4 * SPLIT)) {
                if (lane == 0) {
                    mbar_expect_tx(sbase + OFF_BAR + MB_CNT * 8, 0);
                    bump_counter(&p.sc->cnt);
                }
                *(uint2*)(p.sc->qA + vid * 64 + lane * 2) = make_uint2(0, 0);
                *(uint4*)(p.sc->qabs + vid * 256 + lane * 4) = make_uint4(0, 0, 0, 0);
                *(uint4*)(p.sc->qabs + vid * 256 + 128 + lane * 4) = make_uint4(0, 0, 0, 0);
                counted = true;
            }
        }
        if (look) {
            if (lane == 0) {
                if (!isA && old + (cur - last) == I_BOX * NB) p.sc->prog = 0;
                if (old > prev && old >= 6 * NB && old < (I_BOX - 2) * NB) {
                    const int zn = clock_after(old) - old * TUNED(TAU) / NB + ((vid >> 4) & 7) * TUNED(STAG);
                    z = prev && zn - z < TUNED(JUMP) ? z + ((zn - z) >> TUNED(GAIN)) : zn;
                    prev = old;
                    sts_volatile2(sbase + OFF_WIN, old < TUNED(IMIN) * NB ? TUNED(WMIN0) : TUNED(WMIN), z);
                }
            }
            t1 = now;
        } else {
            __nanosleep(TUNED(SVC));
        }
        last = cur;
        if (spins > SPIN_LIMIT) __trap();
    }
}

__device__ __forceinline__ void softmax_A(const Params& p, char* smem, int w, int lane, int ab, int asp) {
    const int mat = lane >> 3, r = lane & 7;
    float m_run[4], l_run[4];
#pragma unroll
    for (int i = 0; i < 4; i++) { m_run[i] = -INFINITY; l_run[i] = 0.f; }
    const float* red = (const float*)(smem + OFF_ARED);
    for (int k = 0; k < ATILES; k++) {
        bar_sync(BAR_R, 352);
        float4 s[4];
        float mt[4];
#pragma unroll
        for (int i = 0; i < 4; i++) {
            const float* src = red + (16 * w + 4 * i + mat) * 40 + 4 * r;
            const float4 a = *(const float4*)src, b = *(const float4*)(src + 32 * 40);
            const float4 c = *(const float4*)(src + 64 * 40), d = *(const float4*)(src + 96 * 40);
            const uint32_t v0 = score_round2((a.x + b.x) + (c.x + d.x), (a.y + b.y) + (c.y + d.y));
            const uint32_t v1 = score_round2((a.z + b.z) + (c.z + d.z), (a.w + b.w) + (c.w + d.w));
            s[i] = make_float4(bf_lo(v0), bf_hi(v0), bf_lo(v1), bf_hi(v1));
            mt[i] = fmaxf(fmaxf(s[i].x, s[i].y), fmaxf(s[i].z, s[i].w));
        }
#pragma unroll
        for (int o = 1; o < 8; o <<= 1)
#pragma unroll
            for (int i = 0; i < 4; i++) mt[i] = fmaxf(mt[i], __shfl_xor_sync(0xffffffffu, mt[i], o));
#pragma unroll
        for (int i = 0; i < 4; i++) {
            const int head = 16 * w + 4 * i + mat;
            const float m_new = fmaxf(m_run[i], mt[i]);
            const float al = ex2((m_run[i] - m_new) * LOG2E);
            const float e0 = ex2((s[i].x - m_new) * LOG2E), e1 = ex2((s[i].y - m_new) * LOG2E);
            const float e2 = ex2((s[i].z - m_new) * LOG2E), e3 = ex2((s[i].w - m_new) * LOG2E);
            l_run[i] = l_run[i] * al + (e0 + e1) + (e2 + e3);
            m_run[i] = m_new;
            *(uint2*)(smem + OFF_AP + (k & 1) * 2560 + head * 80 + r * 8) = make_uint2(pack_bf16(e0, e1), pack_bf16(e2, e3));
            if (r == 0) ((float*)(smem + OFF_AALPHA))[(k & 1) * 32 + head] = al;
        }
        bar_arrive(BAR_P, 320);
    }
#pragma unroll
    for (int i = 0; i < 4; i++) {
        float l = l_run[i];
        l += __shfl_xor_sync(0xffffffffu, l, 1);
        l += __shfl_xor_sync(0xffffffffu, l, 2);
        l += __shfl_xor_sync(0xffffffffu, l, 4);
        if (r == 0) p.sc->ml[((16 * w + 4 * i + mat) * SPLIT + asp) * 4 + ab] = make_float2(m_run[i], l);
    }
    bar_arrive(BAR_E, 320);
}

__device__ __forceinline__ void attention_A(const Params& p, char* smem, int sw, int lane, int ab, int asp, bool idle_before) {
    const uint32_t sbase = smem_u32(smem);
    const int tid = sw * 32 + lane;
    const int g = lane >> 2, t = lane & 3, mat = lane >> 3, r = lane & 7;
    const int mi = sw & 1, cq = sw >> 1;
    uint4 qf[8];
    {
        const unsigned* src = p.sc->qabs + ab * 8192 + sw * 1024 + lane * 4;
        for (int k = 0; k < (idle_before ? TUNED(ASLEEP) : TUNED(ASLEEP2)); k++) __nanosleep(1000);
        ll_poll4(qf, src, 128, 500);
        if (sw == 0) PROF(6);
    }
    bar_sync(BAR_S, NSW * 32);
    float oacc[2][8][4];
#pragma unroll
    for (int a = 0; a < 2; a++)
#pragma unroll
        for (int b = 0; b < 8; b++) zero4(oacc[a][b]);
    float* red = (float*)(smem + OFF_ARED) + (cq * 32 + 16 * mi + g) * 40 + 2 * t;
    const uint32_t qk_off = sbase + 2 * cq * 4096 + ((mat >> 1) * 8 + r) * 128 + (((mat & 1) ^ r) << 4);
    const uint32_t pv_off = sbase + sw * 4096 + ((mat & 1) * 8 + r) * 128 + (((mat >> 1) ^ r) << 4);
    const uint32_t p_off = sbase + OFF_AP + ((mat & 1) * 8 + r) * 80 + (mat >> 1) * 16;
    int st = 0, ph = 0, stp = 0;
    for (int k = -1; k < ATILES; k++) {
        float sacc[4][4];
        if (k + 1 < ATILES) {
            mbar_wait(sbase + OFF_BAR + (MB_AFULL + st) * 8, ph);
            if (k == -1 && sw == 0) PROF(13);
#pragma unroll
            for (int a = 0; a < 4; a++) zero4(sacc[a]);
#pragma unroll
            for (int ks = 0; ks < 8; ks++) {
#pragma unroll
                for (int np = 0; np < 2; np++) {
                    uint32_t b0, b1, b2, b3;
                    ldsm4(b0, b1, b2, b3, (qk_off ^ ((ks & 3) << 5)) + st * 32768 + (ks >> 2) * 4096 + np * 2048);
                    mma(sacc[2 * np], qf[ks].x, qf[ks].y, qf[ks].z, qf[ks].w, b0, b1);
                    mma(sacc[2 * np + 1], qf[ks].x, qf[ks].y, qf[ks].z, qf[ks].w, b2, b3);
                }
            }
        }
        if (k >= 0) bar_sync(BAR_P, 320);
        if (k + 1 < ATILES) {
#pragma unroll
            for (int nt = 0; nt < 4; nt++) {
                *(float2*)(red + 8 * nt) = make_float2(sacc[nt][0], sacc[nt][1]);
                *(float2*)(red + 8 * nt + 8 * 40) = make_float2(sacc[nt][2], sacc[nt][3]);
            }
            bar_arrive(BAR_R, 352);
        }
        if (k >= 0) {
            const float* alpha = (const float*)(smem + OFF_AALPHA) + (k & 1) * 32;
            const float al0 = alpha[g], al1 = alpha[g + 8], al2 = alpha[g + 16], al3 = alpha[g + 24];
            if (!__all_sync(0xffffffffu, al0 == 1.f && al1 == 1.f && al2 == 1.f && al3 == 1.f)) {
#pragma unroll
                for (int nt = 0; nt < 8; nt++) {
                    oacc[0][nt][0] *= al0; oacc[0][nt][1] *= al0; oacc[0][nt][2] *= al1; oacc[0][nt][3] *= al1;
                    oacc[1][nt][0] *= al2; oacc[1][nt][1] *= al2; oacc[1][nt][2] *= al3; oacc[1][nt][3] *= al3;
                }
            }
#pragma unroll
            for (int ks = 0; ks < 2; ks++) {
                uint32_t pa[2][4];
#pragma unroll
                for (int mt = 0; mt < 2; mt++)
                    ldsm4(pa[mt][0], pa[mt][1], pa[mt][2], pa[mt][3], p_off + (k & 1) * 2560 + mt * 16 * 80 + ks * 32);
#pragma unroll
                for (int np = 0; np < 4; np++) {
                    uint32_t b0, b1, b2, b3;
                    ldsm4t(b0, b1, b2, b3, (pv_off ^ (np << 5)) + stp * 32768 + ks * 2048);
#pragma unroll
                    for (int mt = 0; mt < 2; mt++) {
                        mma(oacc[mt][2 * np], pa[mt][0], pa[mt][1], pa[mt][2], pa[mt][3], b0, b1);
                        mma(oacc[mt][2 * np + 1], pa[mt][0], pa[mt][1], pa[mt][2], pa[mt][3], b2, b3);
                    }
                }
            }
        }
        stp = st;
        if (++st == ASTAGES) { st = 0; ph ^= 1; }
    }
    if (sw == 0) PROF(14);
    {
        float dep = 0.f;
#pragma unroll
        for (int nt = 0; nt < 8; nt++) dep += oacc[1][nt][0];
        warp_release(sbase + OFF_BAR + MB_F3 * 8, lane, dep);
    }
#pragma unroll
    for (int mt = 0; mt < 2; mt++)
#pragma unroll
        for (int hh = 0; hh < 2; hh++) {
            float4* op = (float4*)(p.sc->opart + ((16 * mt + 8 * hh + g) * SPLIT + asp) * 2048 + sw * 256 + ab * 64) + t;
#pragma unroll
            for (int q = 0; q < 4; q++)
                op[4 * q] = make_float4(oacc[mt][2 * q][2 * hh], oacc[mt][2 * q][2 * hh + 1],
                                    oacc[mt][2 * q + 1][2 * hh], oacc[mt][2 * q + 1][2 * hh + 1]);
        }
    bar_sync(BAR_E, 320);
    if (tid == 0) signal_counter(&p.sc->cnt);
    if (sw == 0) PROF(7);
}

__device__ __forceinline__ float matvec64(char* smem, const uint32_t (&xf)[4][2], int mb_full, int mb_free, int sw, int lane) {
    const uint32_t sbase = smem_u32(smem);
    const int g = lane >> 2, t = lane & 3, mat = lane >> 3, r = lane & 7;
    const uint32_t a = sbase + BLK_W + sw * 8192 + ((mat >> 1) * 8 + r) * 128 + (((mat & 1) ^ r) << 4);
    float c[4][4];
#pragma unroll
    for (int mt = 0; mt < 4; mt++) zero4(c[mt]);
    mbar_wait(sbase + OFF_BAR + (mb_full + (sw >> 1)) * 8, 0);
#pragma unroll
    for (int ks = 0; ks < 4; ks++)
#pragma unroll
        for (int mt = 0; mt < 4; mt++) {
            uint32_t a0, a1, a2, a3;
            ldsm4t(a0, a1, a2, a3, (a ^ (mt << 5)) + ks * 2048);
            mma(c[mt], a0, a1, a2, a3, xf[ks][0], xf[ks][1]);
        }
    warp_release(sbase + OFF_BAR + mb_free * 8, lane, (c[0][0] + c[1][0]) + (c[2][0] + c[3][0]));
    float* rp = (float*)(smem + OFF_RED);
#pragma unroll
    for (int mt = 0; mt < 4; mt++) {
        const float y0 = (t < 2 ? c[mt][0] : c[mt][2]) + __shfl_xor_sync(0xffffffffu, t < 2 ? c[mt][2] : c[mt][0], 2);
        const float y1 = (t < 2 ? c[mt][1] : c[mt][3]) + __shfl_xor_sync(0xffffffffu, t < 2 ? c[mt][3] : c[mt][1], 2);
        float* d = rp + sw * 256 + (t & 1) * 128 + 16 * mt + (t >> 1) * 8 + g;
        d[0] = y0;
        d[64] = y1;
    }
    bar_sync(BAR_S, NSW * 32);
    float y = 0.f;
#pragma unroll
    for (int i = 0; i < NSW; i++) y += rp[i * 256 + sw * 32 + lane];
    return y;
}
__device__ __forceinline__ void load_xfrags(const char* smem, uint32_t (&xf)[4][2], int sw, int lane) {
    const uint32_t* x32 = (const uint32_t*)(smem + OFF_X) + ((lane >> 2) & 3) * 256 + 32 * sw + (lane & 3);
#pragma unroll
    for (int ks = 0; ks < 4; ks++) {
        xf[ks][0] = lane < 16 ? x32[ks * 8] : 0u;
        xf[ks][1] = lane < 16 ? x32[ks * 8 + 4] : 0u;
    }
}
__device__ __forceinline__ int vec_word(int vid, int tid) { return (tid >> 6) * 2048 + (vid >> 1) * 32 + ((tid & 63) >> 1); }
__device__ __forceinline__ void store_vec(unsigned* dst, int vid, int tid, float y) {
    const float y1 = __shfl_down_sync(0xffffffffu, y, 1);
    if (!(tid & 1)) ll_store(dst + vec_word(vid, tid), pack_bf16(y, y1));
}
__device__ __forceinline__ void fill_qtab(const Params& p, char* smem, bool isA, int wk, int vid, int tid) {
    const int r = 1 + (tid >> 4);
    uint4 v[1];
    const bool used = (!isA || r >= R_JOIN) && (vid >= 0 || r < R_LATE);
    const int pair = chunk_of(used ? r : R_JOIN, wk, vid) >> 4;
    ll_poll4(v, p.sc->qB + pair * 64 + (tid & 15) * 4, 0, 300);
    *(uint4*)(smem + OFF_Q + 256 + tid * 16) = v[0];
    __syncwarp();
    if ((tid & 31) == 0) mbar_expect_tx(smem_u32(smem) + OFF_BAR + MB_Q * 8, 0);
}
__device__ __forceinline__ void clear_handoffs(const Params& p, int vid, int tid) {
    const int chunk = chunk_of(R_LATE, 0, vid);
    if (tid < 32) *(uint4*)(p.sc->part + chunk * 128 + tid * 4) = make_uint4(0, 0, 0, 0);
    if (tid == 32) *(uint2*)(p.sc->pml + chunk * 2) = make_uint2(0, 0);
    if ((tid >> 4) == 4 && vid < N_EARLY) *(uint4*)(p.sc->oB + vid * 64 + (tid & 15) * 4) = make_uint4(0, 0, 0, 0);
    if ((tid >> 2) == 24) *(uint4*)(p.out + vid * 32 + (tid & 3) * 8) = make_uint4(0, 0, 0, 0);
    if (!((vid | tid) & 1)) p.sc->ctx[vec_word(vid, tid)] = 0;
}
__device__ __forceinline__ void side_prologue(const Params& p, char* smem, bool isA, int wk, int vid, int sw, int lane) {
    const uint32_t sbase = smem_u32(smem);
    const uint32_t bars = sbase + OFF_BAR;
    const int h = vid & 31, j = vid >> 5;
    const int tid = sw * 32 + lane;
    const int g = lane >> 2, t = lane & 3, mat = lane >> 3, r = lane & 7;
    {
        uint32_t xf[4][2];
        mbar_wait(bars + MB_X * 8, 0);
        load_xfrags(smem, xf, sw, lane);
        if (sw == 0) PROF(16);
        store_vec((vid & 1) ? p.sc->qA : p.sc->qB, vid, tid, matvec64(smem, xf, MB_SIDE + SI_WQ, MB_F0, sw, lane));
        if (sw == 0) PROF(18);
    }
    if (tid == 255) asm volatile("fence.acq_rel.gpu;" ::: "memory");
    __syncwarp();
    __nanosleep(TUNED(GSLEEP));
    if (tid < 64) {
        uint4 v[1];
        ll_poll4(v, p.sc->qA + (tid >> 4) * 2048 + h * 64 + (tid & 15) * 4, 0, 300);
        *(uint4*)(smem + OFF_VEC + (tid >> 4) * 272 + (tid & 15) * 16) = v[0];
    }
    fill_qtab(p, smem, isA, wk, vid, tid);
    bar_sync(BAR_S, NSW * 32);
    if (sw == 0) PROF(21);
    {
        mbar_wait(bars + (MB_SIDE + SI_WUK) * 8, 0);
        mbar_wait(bars + (MB_SIDE + SI_WUK + 1) * 8, 0);
        float c2[2][4];
        zero4(c2[0]); zero4(c2[1]);
        const uint32_t* qa = (const uint32_t*)(smem + OFF_VEC + (g & 3) * 272) + t;
        const uint32_t a = sbase + BLK_U + sw * 2048 + ((mat >> 1) * 8 + r) * 128 + (((mat & 1) ^ r) << 4);
#pragma unroll
        for (int ks = 0; ks < 8; ks++) {
            uint32_t b0, b1, b2, b3;
            ldsm4(b0, b1, b2, b3, (a ^ ((ks & 3) << 5)) + (ks >> 2) * 16384);
            const uint32_t a0 = qa[ks * 8], a2 = qa[ks * 8 + 4];
            mma(c2[0], a0, 0, a2, 0, b0, b1);
            mma(c2[1], a0, 0, a2, 0, b2, b3);
        }
        warp_release(bars + MB_FU * 8, lane, c2[0][0] + c2[1][0]);
        ll_store(p.sc->qabs + qabs_word(g & 3, h, j, sw, g >> 2, t),
                 g < 4 ? pack_bf16(c2[0][0], c2[0][1]) : pack_bf16(c2[1][0], c2[1][1]));
    }
    if (sw == 0) PROF(5);
}

__device__ __forceinline__ void side_epilogue(const Params& p, char* smem, int vid, int sw, int lane) {
    const uint32_t sbase = smem_u32(smem);
    const uint32_t bars = sbase + OFF_BAR;
    const int tid = sw * 32 + lane;
    const int g = lane >> 2, t = lane & 3;
    mbar_wait(bars + MB_CNT * 8, 0);
    if (sw == 0) PROF(8);
    if (!(vid & 1)) {
        uint32_t of[4][2];
        const int h = vid >> 2;
        const int b = g & 3, sp = g >> 2;
        float wgt[SPLIT / 2];
        {
            float2 ml[SPLIT / 2];
            float M = -INFINITY, L = 0.f;
#pragma unroll
            for (int q = 0; q < SPLIT / 2; q++) { ml[q] = __ldcg(&p.sc->ml[(h * SPLIT + sp + 2 * q) * 4 + b]); M = fmaxf(M, ml[q].x); }
            M = fmaxf(M, __shfl_xor_sync(0xffffffffu, M, 16));
#pragma unroll
            for (int q = 0; q < SPLIT / 2; q++) { wgt[q] = ex2((ml[q].x - M) * LOG2E); L = fmaf(wgt[q], ml[q].y, L); }
            L += __shfl_xor_sync(0xffffffffu, L, 16);
#pragma unroll
            for (int q = 0; q < SPLIT / 2; q++) { wgt[q] /= L; mbar_wait(bars + (MB_SIDE + SI_OPART + q) * 8, 0); }
        }
#pragma unroll
        for (int ks = 0; ks < 4; ks++) {
            float v[4] = {0.f, 0.f, 0.f, 0.f};
#pragma unroll
            for (int q = 0; q < SPLIT / 2; q++) {
                const float4 u = *((const float4*)(smem + BLK_U) + (sp + 2 * q) * 512 + sw * 64 + b * 16 + 4 * ks + t);
                v[0] = fmaf(u.x, wgt[q], v[0]); v[1] = fmaf(u.y, wgt[q], v[1]);
                v[2] = fmaf(u.z, wgt[q], v[2]); v[3] = fmaf(u.w, wgt[q], v[3]);
            }
#pragma unroll
            for (int e = 0; e < 4; e++) v[e] += __shfl_xor_sync(0xffffffffu, v[e], 16);
#pragma unroll
            for (int hh = 0; hh < 2; hh++) {
                const uint32_t hi = pack_bf16(v[2 * hh], v[2 * hh + 1]);
                of[ks][hh] = sp == 0 ? hi : pack_bf16(v[2 * hh] - bf_lo(hi), v[2 * hh + 1] - bf_hi(hi));
            }
        }
        store_vec(p.sc->ctx, vid, tid, matvec64(smem, of, MB_SIDE + SI_WE, MB_F2, sw, lane));
        if (sw == 0) PROF(9);
    }
    const bool isB = !(vid & 1), late = isB && tid >= 240;
    const unsigned* xs = (isB ? p.sc->oB : p.sc->ctx) + (tid >> 4) * 512 + (vid >> 4) * 64 + (tid & 15) * 4;
    const uint32_t xa = sbase + OFF_X + t * (4 * XROW) + (lane & 8) * 4 + (lane & 16);
    const uint32_t wa = sbase + BLK_W + lane * 128 + ((sw ^ (lane & 7)) << 4);
    const uint32_t va = sbase + OFF_RING + (sw >> 2) * 8192 + ((lane >> 4) * 8 + (lane & 7)) * 128 + (((2 * (sw & 3) + (g >> 1 & 1)) ^ (lane & 7)) << 4);
    uint32_t* out = (uint32_t*)(p.out + (g & 3) * 1024 + (isB ? 512 : 0) + ((vid >> 1) & 7) * 64 + 8 * sw) + t;
    unsigned* lp = p.sc->part + late_pair(vid) * 2048 + 16 * sw;
    unsigned* lm = p.sc->pml + late_pair(vid) * 32;
    const uint4* lf = (const uint4*)(smem + OFF_X + 4 * (3 * XROW + 192)) + t;
    __nv_bfloat16* lx = (__nv_bfloat16*)(smem + OFF_X) + 2 * (3 * XROW + 192) + 32 * (sw >> 1) + 16 * (t & 1) + ((lane & 16) >> 1) +
                        2 * (t & 2) + 2 * (sw & 1) + ((lane >> 3) & 1);
#pragma unroll 1
    for (int pass = 0; pass < 2; pass++) {
        const uint32_t wo = bars + (pass ? MB_SIDE + SI_WO : MB_X) * 8, vf = bars + (pass ? MB_FULL : MB_X) * 8;
        uint4 v = make_uint4(1, 1, 1, 1), u0 = v, u1 = v;
        uint2 m0 = make_uint2(1, 1), m1 = m0;
        {
            mbar_wait(bars + (pass ? MB_PH : MB_CNT) * 8, 0);
            const float4 ma = *(const float4*)(smem + OFF_MLO), mb = *(const float4*)(smem + OFF_MLO + 16);
            const float M = fmaxf(fmaxf(ma.x, ma.z), fmaxf(mb.x, mb.z));
            const float a[4] = {ex2((ma.x - M) * LOG2E), ex2((ma.z - M) * LOG2E), ex2((mb.x - M) * LOG2E), ex2((mb.z - M) * LOG2E)};
            if (pass && tid == 0)
                ll_store2(lm + 2 * (vid & 15), __float_as_uint(M), __float_as_uint((a[0] * ma.y + a[1] * ma.w) + (a[2] * mb.y + a[3] * mb.w)));
            const int done = lds_volatile(sbase + OFF_DONE);
            float f = 0.f;
#pragma unroll
            for (int u = 0; u < 4; u++) {
                const uint4 p0 = *(const uint4*)(smem + OFF_PH + u * 128 + t * 32), p1 = *(const uint4*)(smem + OFF_PH + u * 128 + t * 32 + 16);
                const uint32_t pb[4][2] = {{p0.x, p0.y}, {p0.z, p0.w}, {p1.x, p1.y}, {p1.z, p1.w}};
                float c[4][4];
                mbar_wait(vf + u * 8, 0);
                if (sw == 0) PROF(u < 2 ? 19 + u : u);
#pragma unroll
                for (int k = 0; k < 4; k++) {
                    uint32_t a0, a1, a2, a3;
                    ldsm4t(a0, a1, a2, a3, va + u * TILE_BYTES + k * 2048);
                    zero4(c[k]);
                    mma(c[k], a0, a1, a2, a3, pb[k][0], pb[k][1]);
                }
                const float f0 = (c[0][0] + c[1][0]) + (c[2][0] + c[3][0]), f1 = (c[0][2] + c[1][2]) + (c[2][2] + c[3][2]);
                f = fmaf(a[u], (t & 1) ? f1 : f0, f);
                if (u == 3 && pass && t < 2) ll_store(lp + (vid & 15) * 128 + 8 * t + g, __float_as_uint(f));
                if (pass && tid == 0) sts_volatile(sbase + OFF_DONE, done + u + 1);
                if (u == TUNED(GO) && pass) {
                    if (!late) v = ll_load4(xs);
                    if (isB) { m0 = ll_load2(lm + 2 * g); m1 = ll_load2(lm + 2 * g + 16); }
                }
            }
            if (sw == 0) PROF(10);
        }
        for (unsigned spins = 0; !(ll_ok4(v) && ll_ok4(make_uint4(m0.x, m0.y, m1.x, m1.y))); spins++) {
            __nanosleep(200);
            if (!late) v = ll_load4(xs);
            if (isB) { m0 = ll_load2(lm + 2 * g); m1 = ll_load2(lm + 2 * g + 16); }
            if (spins > SPIN_LIMIT) __trap();
        }
        __syncwarp();
        if (!late) *(uint4*)(smem + OFF_X + (tid >> 6) * (4 * XROW) + (tid & 63) * 16) = make_uint4(~v.x, ~v.y, ~v.z, ~v.w);
        bar_sync(BAR_S, NSW * 32);
        if (sw == 0) PROF(15);
        float w0, w1;
        {
            const float a0 = __uint_as_float(~m0.x), a1 = __uint_as_float(~m1.x), M = redux_max(fmaxf(a0, a1));
            w0 = ex2((a0 - M) * LOG2E), w1 = ex2((a1 - M) * LOG2E);
            float l = w0 * __uint_as_float(~m0.y) + w1 * __uint_as_float(~m1.y);
#pragma unroll
            for (int k = 4; k < 32; k <<= 1) l += __shfl_xor_sync(0xffffffffu, l, k);
            w0 = __fdividef(w0, l), w1 = __fdividef(w1, l);
            if (pass && sw == 0 && !(vid & 15)) *(uint2*)(p.sc->qB + late_pair(vid) * 64 + 2 * lane) = make_uint2(0, 0);
        }
        float acc[4][4];
#pragma unroll
        for (int k = 0; k < 4; k++) zero4(acc[k]);
        uint32_t xf[4][4][4], b[4][4];
        auto rows = [&](int q) {
#pragma unroll
            for (int k = 0; k < 4; k++) ldsm4(xf[q][k][0], xf[q][k][1], xf[q][k][2], xf[q][k][3], xa + q * 256 + k * 64);
        };
        auto load = [&](int q, int h) {
#pragma unroll
            for (int k = 2 * h; k < 2 * h + 2; k++) ldsm4t(b[k][0], b[k][1], b[k][2], b[k][3], wa + q * TILE_BYTES + k * 4096);
        };
        auto mult = [&](int q) {
#pragma unroll
            for (int k = 0; k < 8; k++)
                mma(acc[k & 3], xf[q][k >> 1][0], xf[q][k >> 1][1], xf[q][k >> 1][2], xf[q][k >> 1][3], b[k >> 1][2 * (k & 1)], b[k >> 1][2 * (k & 1) + 1]);
        };
        rows(0); rows(1); rows(2); rows(3);
        mbar_wait(wo, 0);
        load(0, 0); load(0, 1); mult(0);
        if (isB) {
            const int z = lds_volatile(sbase + OFF_WIN + 4) + TUNED(TRIG) * TUNED(TAU) / 4;
            for (int k = pass ? 0 : 63; k < 64 && !__any_sync(0xffffffffu, (int)(now_ns() - z) >= 0); k++) __nanosleep(20);
            if (sw == 0) PROF(27);
            if (pass) { u0 = ll_load4(lp + g * 128 + 4 * t); u1 = ll_load4(lp + g * 128 + 4 * t + 1024); }
        }
        mbar_wait(wo + 8, 0);
        load(1, 0); load(1, 1); mult(1);
        if (isB) {
            for (unsigned spins = 0; !__all_sync(0xffffffffu, ll_ok4(u0) && ll_ok4(u1)); spins++) {
                if (sw == 0 && spins < 3) PROF2(150 + spins);
                u0 = ll_load4(lp + g * 128 + 4 * t); u1 = ll_load4(lp + g * 128 + 4 * t + 1024);
                if (spins > SPIN_LIMIT) __trap();
            }
            if (sw == 0) PROF2(153);
            const float o0 = w0 * __uint_as_float(~u0.x) + w1 * __uint_as_float(~u1.x), o1 = w0 * __uint_as_float(~u0.y) + w1 * __uint_as_float(~u1.y);
            const float o2 = w0 * __uint_as_float(~u0.z) + w1 * __uint_as_float(~u1.z), o3 = w0 * __uint_as_float(~u0.w) + w1 * __uint_as_float(~u1.w);
            const bool hi = lane & 16, mid = lane & 8;
            const float e0 = (hi ? o2 : o0) + __shfl_xor_sync(0xffffffffu, hi ? o0 : o2, 16);
            const float e1 = (hi ? o3 : o1) + __shfl_xor_sync(0xffffffffu, hi ? o1 : o3, 16);
            const float e = (mid ? e1 : e0) + __shfl_xor_sync(0xffffffffu, mid ? e0 : e1, 8);
            *lx = __float2bfloat16_rn(e + __shfl_xor_sync(0xffffffffu, e, 4));
            if (sw == 0) PROF(4);
        }
        bool r2 = mbar_test(wo + 16, 0);
        if (isB) bar_sync(BAR_S, NSW * 32);
        if (isB && g == 3) {
#pragma unroll
            for (int k = 0; k < 4; k++) {
                const uint4 f = lf[4 * k];
                xf[3][k][0] = f.x; xf[3][k][1] = f.y; xf[3][k][2] = f.z; xf[3][k][3] = f.w;
            }
        }
        mbar_wait_unless(r2, wo + 16);
        bool r3 = mbar_test(wo + 24, 0);
        load(2, 0); load(2, 1); mult(2);
        mbar_wait_unless(r3, wo + 24);
        r3 = mbar_try(wo + 32, 0);
        load(3, 0);
        mbar_wait_unless(r3, wo + 32);
        if (sw == 0) PROF(11);
        load(3, 1); mult(3);
        const uint32_t y = pack_bf16((acc[0][0] + acc[1][2]) + (acc[2][0] + acc[3][2]), (acc[0][1] + acc[1][3]) + (acc[2][1] + acc[3][3]));
        asm volatile("{\n .reg .pred q;\n setp.ne.u32 q, %2, 0;\n @q red.relaxed.gpu.global.add.noftz.bf16x2 [%0], %1;\n}"
                     ::"l"(out), "r"(y), "r"((int)(pass && lane < 16)) : "memory");
    }
    if (sw == 7) PROF(25);
    if (sw == 2) PROF(24);
}

__global__ void __launch_bounds__(NTHREADS, 1) fused_decode_kernel(const Ptrs ptrs, const __grid_constant__ Maps maps) {
    extern __shared__ __align__(1024) char smem[];
    Params p;
    static_cast<Ptrs&>(p) = ptrs;
    p.tm = maps.tm;
    const unsigned blk = blockIdx.x;
    asm volatile("{\n .reg .u64 a;\n mad.wide.u32 a, %1, 32, %0;\n prefetch.global.L2 [a];\n}" ::"l"(p.K), "r"(blk * NTHREADS + threadIdx.x) : "memory");
    if (threadIdx.x == 0) first_load(p, smem_u32(smem), blk);
    const int warp = __shfl_sync(0xffffffffu, threadIdx.x >> 5, 0), lane = threadIdx.x & 31;
    const bool isA = blk % APER == APER - 1;
    const int aidx = blk / APER, ab = aidx / SPLIT, asp = aidx % SPLIT;
    const int wk = isA ? NB + aidx : blk - aidx;
    const int vid = !isA ? wk : asp == 3 ? -1 : NB + ab * 3 + asp;
    if (threadIdx.x == 32) next_loads(p, smem_u32(smem), vid);
    if (lane == 0 && warp != 1) {
        const int wu = max(warp, 1);
#pragma unroll
        for (int k = 0; k < (MB_COUNT - MB_EARLY + 10) / 11; k++) {
            const int i = MB_EARLY + k * 11 + wu - 1;
            if (i < MB_COUNT && i != MB_FULL) mbar_init(smem_u32(smem) + OFF_BAR + i * 8, i >= MB_F0 ? NSW : i == MB_PH ? 4 : 1);
        }
        fence_mbar_init();
        if (wu >= 2 && wu < 8) asm volatile("prefetch.tensormap [%0];" ::"l"(&p.tm[wu]) : "memory");
    }
    __syncwarp();
    if (threadIdx.x == 33) {
        *(int2*)(smem + OFF_DONE) = make_int2(0, 0);
        *(int2*)(smem + OFF_WIN) = make_int2(TUNED(WSTART), 0);
    }
    if (warp >= 4 && vid >= 0) clear_handoffs(p, vid, threadIdx.x - 128);
    bar_sync(0, NTHREADS);
    if (warp == 0) {
        produce(p, smem, lane, isA, wk, vid, ab * 4096 + asp * 32);
    } else if (warp < 3) {
        if (isA) softmax_A(p, smem, warp - 1, lane, ab, asp);
        consume(p, smem, isA, wk, vid, warp - 1, lane);
    } else if (warp == 3) {
        service(p, smem, isA, vid, lane);
    } else {
        const int sw = warp - 4;
        if (vid >= 0) side_prologue(p, smem, isA, wk, vid, sw, lane);
        if (isA) attention_A(p, smem, sw, lane, ab, asp, vid < 0);
        if (vid < 0) fill_qtab(p, smem, isA, wk, vid, threadIdx.x - 128);
        if (vid >= 0) side_epilogue(p, smem, vid, sw, lane);
    }
}

__device__ float g_tmp[2][4 * 32 * 512];
__device__ __forceinline__ float bfr(float x) { return __bfloat162float(__float2bfloat16_rn(x)); }
template <typename X>
__global__ void fb_matvec(const X* x, int xb, int xh, int K, const __nv_bfloat16* W, int wk, int wh, int wn, float* y,
                          __nv_bfloat16* out, bool round) {
    const int n = threadIdx.x, h = blockIdx.x, b = blockIdx.y;
    float s = 0.f;
    for (int k = 0; k < K; k++) s += (float)x[b * xb + h * xh + k] * __bfloat162float(W[(size_t)k * wk + h * wh + (size_t)n * wn]);
    if (out) out[b * 1024 + n] = __float2bfloat16_rn(s);
    else y[(b * gridDim.x + h) * blockDim.x + n] = round ? bfr(s) : s;
}
__global__ void fb_attn(const float* q, const __nv_bfloat16* K, const __nv_bfloat16* V, int D, size_t sb, size_t sh, float* o, bool round) {
    __shared__ float sc[4096], red[8];
    const int h = blockIdx.x, b = blockIdx.y, tid = threadIdx.x;
    K += b * sb + h * sh; V += b * sb + h * sh; q += (b * 32 + h) * D;
    float m = -INFINITY, l = 0.f;
    for (int k = tid; k < 4096; k += 256) {
        float s = 0.f;
        for (int d = 0; d < D; d++) s += q[d] * __bfloat162float(K[(size_t)k * D + d]);
        m = fmaxf(m, sc[k] = bfr(bfr(s) * SCALE));
    }
    m = warp_max(m);
    if (!(tid & 31)) red[tid >> 5] = m;
    __syncthreads();
    for (int i = 0; i < 8; i++) m = fmaxf(m, red[i]);
    __syncthreads();
    for (int k = tid; k < 4096; k += 256) { const float e = expf(sc[k] - m); l += e; sc[k] = bfr(e); }
    l = warp_sum(l);
    if (!(tid & 31)) red[tid >> 5] = l;
    __syncthreads();
    l = 0.f;
    for (int i = 0; i < 8; i++) l += red[i];
    for (int d = tid; d < D; d += 256) {
        float s = 0.f;
        for (int k = 0; k < 4096; k++) s += sc[k] * __bfloat162float(V[(size_t)k * D + d]);
        o[(b * 32 + h) * D + d] = round ? bfr(s / l) : s / l;
    }
}
void launch_fallback(void* const* d_in, __nv_bfloat16* out) {
    typedef const __nv_bfloat16* BP;
    float* t0;
    cudaGetSymbolAddress((void**)&t0, g_tmp);
    float* t1 = t0 + 4 * 32 * 512;
    const dim3 gh(32, 4), g1(1, 4);
    fb_matvec<<<gh, 128>>>((BP)d_in[0], 512, 0, 512, (BP)d_in[2], 4096, 128, 1, t0, nullptr, true);
    fb_matvec<<<gh, 512>>>((const float*)t0, 4096, 128, 128, (BP)d_in[3], 1, 128, 4096, t1, nullptr, true);
    fb_attn<<<gh, 256>>>(t1, (BP)d_in[1], (BP)d_in[1], 512, (size_t)4096 * 512, 0, t0, false);
    fb_matvec<<<gh, 128>>>((const float*)t0, 32 * 512, 512, 512, (BP)d_in[4], 4096, 128, 1, t1, nullptr, true);
    fb_matvec<<<g1, 512>>>((const float*)t1, 4096, 0, 4096, (BP)d_in[5], 512, 0, 1, nullptr, out, false);
    fb_matvec<<<gh, 128>>>((BP)d_in[6], 512, 0, 512, (BP)d_in[9], 4096, 128, 1, t0, nullptr, true);
    fb_attn<<<gh, 256>>>(t0, (BP)d_in[7], (BP)d_in[8], 128, (size_t)32 * 4096 * 128, (size_t)4096 * 128, t1, true);
    fb_matvec<<<g1, 512>>>((const float*)t1, 4096, 0, 4096, (BP)d_in[10], 512, 0, 1, nullptr, out + 512, false);
}

typedef CUresult (*EncodeFn)(CUtensorMap*, CUtensorMapDataType, cuuint32_t, void*, const cuuint64_t*, const cuuint64_t*,
                             const cuuint32_t*, const cuuint32_t*, CUtensorMapInterleave, CUtensorMapSwizzle,
                             CUtensorMapL2promotion, CUtensorMapFloatOOBfill);

void make_map(EncodeFn enc, CUtensorMap* tm, void* ptr, uint64_t cols, uint64_t rows, uint32_t br) {
    const cuuint64_t dims[2] = {cols, rows};
    const cuuint64_t strides[1] = {cols * 2};
    const cuuint32_t box[2] = {64, br};
    const cuuint32_t es[2] = {1, 1};
    enc(tm, CU_TENSOR_MAP_DATA_TYPE_BFLOAT16, 2, ptr, dims, strides, box, es, CU_TENSOR_MAP_INTERLEAVE_NONE,
        CU_TENSOR_MAP_SWIZZLE_128B, CU_TENSOR_MAP_L2_PROMOTION_NONE,
        CU_TENSOR_MAP_FLOAT_OOB_FILL_NONE);
}

}

extern "C" void kernel_launch(void* const* d_in, const int* in_sizes, int n_in, void* d_out, int out_size) {
    (void)in_sizes; (void)n_in; (void)out_size;
    void* fn = nullptr;
    cudaDriverEntryPointQueryResult qr;
    cudaGetDriverEntryPoint("cuTensorMapEncodeTiled", &fn, cudaEnableDefault, &qr);
    EncodeFn enc = (EncodeFn)fn;
    int dev = 0, sms = 0, per_sm = 0;
    cudaGetDevice(&dev);
    cudaDeviceGetAttribute(&sms, cudaDevAttrMultiProcessorCount, dev);
    cudaFuncSetAttribute(fused_decode_kernel, cudaFuncAttributeMaxDynamicSharedMemorySize, SMEM_BYTES);
    cudaOccupancyMaxActiveBlocksPerMultiprocessor(&per_sm, fused_decode_kernel, NTHREADS, SMEM_BYTES);
    if (!enc || sms * per_sm < NCTA) {
        launch_fallback(d_in, (__nv_bfloat16*)d_out);
        return;
    }
    Ptrs p;
    Maps m;
    make_map(enc, &m.tm[0], d_in[9], 4096, 512, 128);
    make_map(enc, &m.tm[1], d_in[2], 4096, 512, 128);
    make_map(enc, &m.tm[2], d_in[10], 512, 4096, 64);
    make_map(enc, &m.tm[3], d_in[5], 512, 4096, 64);
    make_map(enc, &m.tm[4], d_in[3], 4096, 512, 128);
    make_map(enc, &m.tm[5], d_in[4], 4096, 512, 128);
    make_map(enc, &m.tm[6], d_in[1], 512, 4 * 4096, 32);
    make_map(enc, &m.tm[7], d_in[8], 128, 128 * 4096, TK);
    p.xA = (const __nv_bfloat16*)d_in[0];
    p.xB = (const __nv_bfloat16*)d_in[6];
    p.K = (const __nv_bfloat16*)d_in[7];
    p.V = (const __nv_bfloat16*)d_in[8];
    p.out = (__nv_bfloat16*)d_out;
    cudaGetSymbolAddress((void**)&p.sc, g_scratch);
    fused_decode_kernel<<<NCTA, NTHREADS, SMEM_BYTES>>>(p, m);
}
```

```cpp
#include <cuda.h>
#include <cuda_runtime.h>
#include <cuda_bf16.h>
#include <stdint.h>

namespace {

#define TV_WSTART 3
#define TV_WMIN0 3
#define TV_WMIN 2
#define TV_IMIN 100
#define TV_LEAD 18
#define TV_LEADE 14
#define TV_WMAXE 3
#define TV_IEND 120
#define TV_TAU 640
#define TV_GAIN 1
#define TV_JUMP 400
#define TV_STAG 80
#define TV_QSLEEP 1600
#define TV_GSLEEP 3000
#define TV_ASLEEP 16
#define TV_ASLEEP2 8
#define TV_ITE 6
#define TV_WESTEP 1
#define TV_CNT0 56
#define TV_MERGE 1
#define TV_MERGE0 6
#define TV_SVC 64
#define TV_GO 2
#define TV_TRIG 541
enum { T_WSTART, T_WMIN0, T_WMIN, T_IMIN, T_LEAD, T_LEADE, T_WMAXE, T_IEND, T_TAU, T_GAIN, T_JUMP, T_STAG, T_QSLEEP, T_GSLEEP, T_ASLEEP, T_ASLEEP2, T_ITE, T_WESTEP, T_CNT0, T_MERGE, T_MERGE0, T_SVC, T_GO, T_TRIG, T_COUNT };
#define TUNED(k) (TV_##k)

constexpr int TK = 64;
constexpr int TILE_BYTES = TK * 256;
constexpr int NS = 6;
constexpr int WMAX = 6;
constexpr int NSW = 8;
constexpr int NTHREADS = (4 + NSW) * 32;
constexpr int SPLIT = 4;
constexpr int AKEYS = 4096 / SPLIT;
constexpr int ATILES = AKEYS / 32;
constexpr int ASTAGES = 6;
constexpr int NCTA = 132;
constexpr int APER = 8;
constexpr int NB = NCTA - 4 * SPLIT;
constexpr int R_JOIN = 12, R_LATE = 16, N_EARLY = 120;
static_assert(R_JOIN * NB + (R_LATE - R_JOIN) * NCTA == N_EARLY * 16, "early chunks");
constexpr int I_LAST = 8 * R_LATE + 4;
static_assert(I_LAST % (2 * NS) == 0 && (8 * R_JOIN) % (2 * NS) == 0, "stage and parity of the last tiles");
constexpr int I_BOX = I_LAST + 4;
__device__ __forceinline__ int late_pair(int vid) { return N_EARLY + (vid >> 4); }
__device__ __forceinline__ int chunk_of(int r, int wk, int vid) {
    return r * NB + max(r - R_JOIN, 0) * (NCTA - NB) + (r == R_LATE ? vid : wk);
}

__host__ __device__ constexpr int tiles4(int q) {
    return NB * q + (q > 32 * R_JOIN ? (NCTA - NB) * (q - 32 * R_JOIN) : 0) - (q > 32 * R_LATE ? (NCTA - 128) * (q - 32 * R_LATE) : 0);
}

#define CGRP 16
constexpr int CHUNK_STEP = CGRP * TILE_BYTES;
__device__ __forceinline__ size_t chunk_off(unsigned c) { return (size_t)(4 * c - 3 * (c % CGRP)) * TILE_BYTES; }

constexpr int OFF_RING = 0;
constexpr int OFF_SIDE = NS * TILE_BYTES;
constexpr int OFF_SCR = OFF_SIDE + 98304;
constexpr int OFF_X = OFF_SCR;
constexpr int XROW = 264;
constexpr int OFF_RED = OFF_SCR + 8192;
constexpr int OFF_ARED = OFF_SCR;
constexpr int OFF_AP = OFF_ARED + 4 * 32 * 40 * 4;
constexpr int OFF_AALPHA = OFF_AP + 2 * 32 * 80;
constexpr int OFF_OPART = OFF_AALPHA + 256;
constexpr int OFF_ML = OFF_OPART + 2 * 512;
constexpr int OFF_PH = OFF_ML + 16;
constexpr int OFF_MLO = OFF_PH + 512;
constexpr int OFF_DONE = OFF_MLO + 32;
constexpr int OFF_WIN = OFF_DONE + 8;
constexpr int OFF_VEC = OFF_WIN + 8;
constexpr int OFF_Q = OFF_VEC + 4 * 68 * 4;
constexpr int OFF_BAR = OFF_Q + (R_LATE + 1) * 256;
enum { SI_WQ = 0, SI_WUK = 4, SI_WE = 6, SI_OPART = 10, SI_WO = 12, SI_COUNT = SI_WO + 5 };
enum {
    MB_X = 0, MB_SIDE = 1, MB_EARLY = MB_SIDE + 4,
    MB_FULL = MB_SIDE + SI_COUNT,
    MB_AFULL = MB_FULL + NS,
    MB_CNT = MB_AFULL + ASTAGES,
    MB_PH,
    MB_EMPTY,
    MB_F0 = MB_EMPTY + NS, MB_FU, MB_F2, MB_F3,
    MB_Q,
    MB_COUNT
};
constexpr int SMEM_BYTES = OFF_BAR + MB_COUNT * 8;
static_assert(SMEM_BYTES <= 232448, "smem");
constexpr int BLK_W = OFF_SIDE;
constexpr int BLK_U = OFF_SIDE + 65536;

constexpr int BAR_B = 9  , BAR_S = 2, BAR_R = 5, BAR_P = 6, BAR_E = 7;

constexpr float SCALE = 0.08838834764831845f;
constexpr float LOG2E = 1.4426950408889634f;
constexpr unsigned SPIN_LIMIT = 1u << 22;

struct Scratch {
    float opart[32 * SPLIT * 2048];
    unsigned qB[4 * 2048];
    unsigned qA[4 * 2048];
    unsigned qabs[4 * 8192];
    unsigned ctx[4 * 2048];
    unsigned oB[4 * 2048];
    unsigned part[2048 * 128];
    unsigned pml[2048 * 2];
    float2 ml[32 * SPLIT * 4];
    unsigned prog, pad[31];
    unsigned cnt;
};
__device__ __align__(128) Scratch g_scratch;

struct Ptrs {
    const __nv_bfloat16 *K, *V, *xA, *xB;
    __nv_bfloat16* out;
    Scratch* sc;
};
struct Maps {
    CUtensorMap tm[8];
};
struct Params : Ptrs {
    const CUtensorMap* tm;
};

#define PROF(i)
#define PROF2(i)

__device__ __forceinline__ uint32_t smem_u32(const void* p) { return (uint32_t)__cvta_generic_to_shared(p); }
__device__ __forceinline__ void mbar_init(uint32_t bar, int cnt) {
    asm volatile("mbarrier.init.shared::cta.b64 [%0], %1;" ::"r"(bar), "r"(cnt) : "memory");
}
__device__ __forceinline__ void mbar_expect_tx(uint32_t bar, uint32_t bytes) {
    asm volatile("mbarrier.arrive.expect_tx.shared::cta.b64 _, [%0], %1;" ::"r"(bar), "r"(bytes) : "memory");
}
__device__ __forceinline__ bool mbar_try(uint32_t bar, uint32_t parity) {
    uint32_t ok;
    asm volatile("{\n .reg .pred p;\n mbarrier.try_wait.parity.shared::cta.b64 p, [%1], %2;\n selp.u32 %0, 1, 0, p;\n}"
                 : "=r"(ok) : "r"(bar), "r"(parity) : "memory");
    return ok;
}
__device__ __forceinline__ void mbar_wait(uint32_t bar, uint32_t parity) {
    unsigned spins = 0;
    while (!mbar_try(bar, parity))
        if (++spins > SPIN_LIMIT) __trap();
}
__device__ __forceinline__ void mbar_wait_unless(bool done, uint32_t bar) {
    for (unsigned spins = 0; !done; done = mbar_try(bar, 0))
        if (++spins > SPIN_LIMIT) __trap();
}
__device__ __forceinline__ bool mbar_test(uint32_t bar, uint32_t parity) {
    uint32_t ok;
    asm volatile("{\n .reg .pred p;\n mbarrier.test_wait.parity.shared::cta.b64 p, [%1], %2;\n selp.u32 %0, 1, 0, p;\n}"
                 : "=r"(ok) : "r"(bar), "r"(parity) : "memory");
    return ok;
}
__device__ __forceinline__ void warp_release(uint32_t bar, int lane, float dep) {
    const uint32_t any = __ballot_sync(0xffffffffu, dep != dep);
    if (lane == 0)
        asm volatile("{\n .reg .pred q;\n setp.eq.u32 q, %1, 0;\n @q mbarrier.arrive.shared::cta.b64 _, [%0];\n"
                     " @!q mbarrier.arrive.shared::cta.b64 _, [%0];\n}" ::"r"(bar), "r"(any) : "memory");
}
__device__ __forceinline__ bool elect_one() {
    uint32_t e;
    asm volatile("{\n .reg .pred p;\n elect.sync _|p, 0xffffffff;\n selp.u32 %0, 1, 0, p;\n}" : "=r"(e));
    return e;
}
__device__ __forceinline__ int lds_volatile(uint32_t addr) {
    int v;
    asm volatile("ld.volatile.shared.u32 %0, [%1];" : "=r"(v) : "r"(addr) : "memory");
    return v;
}
__device__ __forceinline__ int2 lds_volatile2(uint32_t addr) {
    int2 v;
    asm volatile("ld.volatile.shared.v2.u32 {%0, %1}, [%2];" : "=r"(v.x), "=r"(v.y) : "r"(addr) : "memory");
    return v;
}
__device__ __forceinline__ void sts_volatile2(uint32_t addr, int a, int b) {
    asm volatile("st.volatile.shared.v2.u32 [%0], {%1, %2};" ::"r"(addr), "r"(a), "r"(b) : "memory");
}
__device__ __forceinline__ void sts_volatile(uint32_t addr, int v) {
    asm volatile("st.volatile.shared.u32 [%0], %1;" ::"r"(addr), "r"(v) : "memory");
}
__device__ __forceinline__ unsigned now_ns() {
    unsigned t;
    asm volatile("mov.u32 %0, %%globaltimer_lo;" : "=r"(t) :: "memory");
    return t;
}
__device__ __forceinline__ int clock_after(unsigned dep) {
    int c;
    asm volatile("{\n .reg .pred q;\n setp.eq.u32 q, %1, 0;\n @q mov.u32 %0, %%globaltimer_lo;\n @!q mov.u32 %0, %%globaltimer_lo;\n}" : "=r"(c) : "r"(dep) : "memory");
    return c;
}
__device__ __forceinline__ void fence_mbar_init() { asm volatile("fence.mbarrier_init.release.cluster;" ::: "memory"); }
__device__ __forceinline__ uint64_t policy_evict_first() {
    uint64_t pol;
    asm volatile("createpolicy.fractional.L2::evict_first.b64 %0, 1.0;" : "=l"(pol));
    return pol;
}
__device__ __forceinline__ uint64_t policy_evict_normal() {
    uint64_t pol;
    asm volatile("createpolicy.fractional.L2::evict_normal.b64 %0, 1.0;" : "=l"(pol));
    return pol;
}
__device__ __forceinline__ void bulk_load(uint32_t dst, const void* src, uint32_t bytes, uint32_t bar, uint64_t pol) {
    asm volatile("cp.async.bulk.shared::cluster.global.mbarrier::complete_tx::bytes.L2::cache_hint [%0], [%1], %2, [%3], %4;"
                 ::"r"(dst), "l"(src), "r"(bytes), "r"(bar), "l"(pol) : "memory");
}
__device__ __forceinline__ void bulk_load_nohint(uint32_t dst, const void* src, uint32_t bytes, uint32_t bar) {
    asm volatile("cp.async.bulk.shared::cluster.global.mbarrier::complete_tx::bytes [%0], [%1], %2, [%3];"
                 ::"r"(dst), "l"(src), "r"(bytes), "r"(bar) : "memory");
}
__device__ __forceinline__ void tma2d_hint(uint32_t dst, const CUtensorMap* tm, int x, int y, uint32_t bar, uint64_t pol) {
    asm volatile("cp.async.bulk.tensor.2d.shared::cluster.global.mbarrier::complete_tx::bytes.L2::cache_hint [%0], [%1, {%3, %4}], [%2], %5;"
                 ::"r"(dst), "l"(tm), "r"(bar), "r"(x), "r"(y), "l"(pol) : "memory");
}
__device__ __forceinline__ void ldsm4(uint32_t& r0, uint32_t& r1, uint32_t& r2, uint32_t& r3, uint32_t addr) {
    asm volatile("ldmatrix.sync.aligned.m8n8.x4.shared.b16 {%0,%1,%2,%3}, [%4];"
                 : "=r"(r0), "=r"(r1), "=r"(r2), "=r"(r3) : "r"(addr) : "memory");
}
__device__ __forceinline__ void ldsm4t(uint32_t& r0, uint32_t& r1, uint32_t& r2, uint32_t& r3, uint32_t addr) {
    asm volatile("ldmatrix.sync.aligned.m8n8.x4.trans.shared.b16 {%0,%1,%2,%3}, [%4];"
                 : "=r"(r0), "=r"(r1), "=r"(r2), "=r"(r3) : "r"(addr) : "memory");
}
__device__ __forceinline__ void mma(float (&c)[4], uint32_t a0, uint32_t a1, uint32_t a2, uint32_t a3, uint32_t b0, uint32_t b1) {
    asm volatile("mma.sync.aligned.m16n8k16.row.col.f32.bf16.bf16.f32 {%0,%1,%2,%3}, {%4,%5,%6,%7}, {%8,%9}, {%0,%1,%2,%3};"
                 : "+f"(c[0]), "+f"(c[1]), "+f"(c[2]), "+f"(c[3])
                 : "r"(a0), "r"(a1), "r"(a2), "r"(a3), "r"(b0), "r"(b1));
}
__device__ __forceinline__ void zero4(float (&c)[4]) { c[0] = c[1] = c[2] = c[3] = 0.f; }
__device__ __forceinline__ void bar_sync(int id, int n) { asm volatile("bar.sync %0, %1;" ::"r"(id), "r"(n) : "memory"); }
__device__ __forceinline__ void bar_arrive(int id, int n) { asm volatile("bar.arrive %0, %1;" ::"r"(id), "r"(n) : "memory"); }
__device__ __forceinline__ float ex2(float x) { float y; asm("ex2.approx.ftz.f32 %0, %1;" : "=f"(y) : "f"(x)); return y; }
__device__ __forceinline__ uint32_t pack_bf16(float lo, float hi) {
    uint32_t r; asm("cvt.rn.bf16x2.f32 %0, %1, %2;" : "=r"(r) : "f"(hi), "f"(lo)); return r;
}
__device__ __forceinline__ float bf_lo(uint32_t u) { return __uint_as_float(u << 16); }
__device__ __forceinline__ float bf_hi(uint32_t u) { return __uint_as_float(u & 0xffff0000u); }
__device__ __forceinline__ uint32_t score_round2(float a, float b) {
    const uint32_t u = pack_bf16(a, b);
    return pack_bf16(bf_lo(u) * SCALE, bf_hi(u) * SCALE);
}
__device__ __forceinline__ float warp_max(float v) {
#pragma unroll
    for (int o = 16; o > 0; o >>= 1) v = fmaxf(v, __shfl_xor_sync(0xffffffffu, v, o));
    return v;
}
__device__ __forceinline__ float redux_max(float v) {
    const int i = __float_as_int(v), m = __reduce_max_sync(0xffffffffu, i ^ ((i >> 31) & 0x7fffffff));
    return __int_as_float(m ^ ((m >> 31) & 0x7fffffff));
}
__device__ __forceinline__ float warp_sum(float v) {
#pragma unroll
    for (int o = 16; o > 0; o >>= 1) v += __shfl_xor_sync(0xffffffffu, v, o);
    return v;
}

__device__ __forceinline__ void ll_store(unsigned* p, unsigned bits) {
    unsigned u = ~bits;
    u = u ? u : 0x80008000u;
    asm volatile("st.relaxed.gpu.global.u32 [%0], %1;" ::"l"(p), "r"(u) : "memory");
}
__device__ __forceinline__ void ll_store2(unsigned* p, unsigned a, unsigned b) {
    unsigned u = ~a, v = ~b;
    u = u ? u : 0x80008000u;
    v = v ? v : 0x80008000u;
    asm volatile("st.relaxed.gpu.global.v2.u32 [%0], {%1, %2};" ::"l"(p), "r"(u), "r"(v) : "memory");
}
__device__ __forceinline__ void ll_store4(unsigned* p, float a, float b, float c, float d) {
    unsigned u[4] = {~__float_as_uint(a), ~__float_as_uint(b), ~__float_as_uint(c), ~__float_as_uint(d)};
#pragma unroll
    for (int k = 0; k < 4; k++) u[k] = u[k] ? u[k] : 0x80008000u;
    asm volatile("st.relaxed.gpu.global.v4.u32 [%0], {%1, %2, %3, %4};" ::"l"(p), "r"(u[0]), "r"(u[1]), "r"(u[2]), "r"(u[3]) : "memory");
}
__device__ __forceinline__ unsigned ll_load(const unsigned* p) {
    unsigned u;
    asm volatile("ld.relaxed.gpu.global.u32 %0, [%1];" : "=r"(u) : "l"(p) : "memory");
    return u;
}
__device__ __forceinline__ uint2 ll_load2(const unsigned* p) {
    uint2 v;
    asm volatile("ld.relaxed.gpu.global.v2.u32 {%0,%1}, [%2];" : "=r"(v.x), "=r"(v.y) : "l"(p) : "memory");
    return v;
}
__device__ __forceinline__ uint4 ll_load4(const unsigned* p) {
    uint4 v;
    asm volatile("ld.relaxed.gpu.global.v4.u32 {%0,%1,%2,%3}, [%4];" : "=r"(v.x), "=r"(v.y), "=r"(v.z), "=r"(v.w) : "l"(p) : "memory");
    return v;
}
__device__ __forceinline__ bool ll_ok4(const uint4& v) { return min(min(v.x, v.y), min(v.z, v.w)) != 0u; }
template <int N>
__device__ __forceinline__ void ll_poll4(uint4 (&v)[N], const unsigned* p, int stride, unsigned sleep_ns = 0) {
    unsigned spins = 0;
    while (true) {
        bool ok = true;
#pragma unroll
        for (int k = 0; k < N; k++) v[k] = ll_load4(p + k * stride);
#pragma unroll
        for (int k = 0; k < N; k++) ok = ok && ll_ok4(v[k]);
        if (ok) break;
        if (sleep_ns) __nanosleep(sleep_ns);
        if (++spins > SPIN_LIMIT) __trap();
    }
    __syncwarp();
#pragma unroll
    for (int k = 0; k < N; k++) v[k] = make_uint4(~v[k].x, ~v[k].y, ~v[k].z, ~v[k].w);
}

__device__ __forceinline__ void bump_counter(unsigned* c) {
    asm volatile("red.relaxed.gpu.global.inc.u32 [%0], %1;" ::"l"(c), "r"(4 * SPLIT + 128 - 1) : "memory");
}
__device__ __forceinline__ void signal_counter(unsigned* c) {
    asm volatile("fence.acq_rel.gpu;" ::: "memory");
    bump_counter(c);
}
__device__ __forceinline__ unsigned ld_acquire(const unsigned* c) {
    unsigned v;
    asm volatile("ld.acquire.gpu.global.u32 %0, [%1];" : "=r"(v) : "l"(c) : "memory");
    return v;
}
__device__ __forceinline__ uint32_t pv_mask(int c, int g, int t) {
    return (c == (g ^ (2 * t)) ? 0x0000ffffu : 0u) | (c == (g ^ (2 * t + 1)) ? 0xffff0000u : 0u);
}

struct Producer {
    uint32_t sbase;
    uint32_t wbar, wpar;
    bool pend;
    int lane;
    uint64_t pol;
    uint32_t si_dst, si_gate;
    int si_x, si_y, si_min;
    bool si_box;
    const void* si_src;
    uint64_t si_pol;
    __device__ __forceinline__ uint32_t mb(int i) const { return sbase + OFF_BAR + i * 8; }
    __device__ __forceinline__ void setup_side(const Params& p, int vid) {
        const int cbk = vid >> 1, u = lane & 1;
        si_box = true; si_min = 0; si_gate = mb(MB_X);
        si_pol = lane >= SI_OPART ? policy_evict_normal() : pol;
        int blk = BLK_U + u * 16384;
        if (lane >= SI_OPART) {
            si_box = false; si_src = p.sc->opart + ((cbk >> 1) * SPLIT + 2 * u) * 2048;
            si_gate = mb(MB_CNT);
        } else if (lane >= SI_WE) {
            const int q = lane - SI_WE;
            si_src = &p.tm[5]; blk = BLK_W + q * 16384;
            si_x = 64 * cbk; si_y = 128 * q;
            si_gate = mb(MB_F0); si_min = TUNED(ITE) + TUNED(WESTEP) * q;
        } else {
            si_src = &p.tm[4]; si_x = (vid & 31) * 128 + 64 * u; si_y = 128 * (vid >> 5);
        }
        si_dst = sbase + blk;
    }
    __device__ __forceinline__ bool due(const Params& p, int i, int2 st) const {
        return st.y && (int)(now_ns() - st.y) >= tiles4(4 * i - (i < TUNED(IEND) ? TUNED(LEAD) : TUNED(LEADE))) * TUNED(TAU) / 512;
    }
    __device__ __forceinline__ void window(const Params& p, int i, uint32_t bar, uint32_t parity) {
        unsigned busy;
        for (unsigned spins = 0;; spins++) {
            const int2 st = lds_volatile2(sbase + OFF_WIN);
            if (pend) pend = !mbar_test(wbar, wpar);
            busy = __ballot_sync(0xffffffffu, pend);
            const int n = __popc(busy);
            if (__any_sync(0xffffffffu, n < st.x || (n < (i < TUNED(IEND) ? WMAX : TUNED(WMAXE)) && due(p, i, st)))) break;
            if (spins > 16 * SPIN_LIMIT) __trap();
        }
        if (lane == __ffs(~busy) - 1) { wbar = bar; wpar = parity; pend = true; }
    }
    __device__ __forceinline__ void side(const Params& p, int id) {
        const uint32_t bar = mb(MB_SIDE + id);
        if (id < SI_OPART) window(p, 0, bar, 0);
        if (lane == id) {
            mbar_expect_tx(bar, TILE_BYTES);
            if (si_box) {
                tma2d_hint(si_dst, (const CUtensorMap*)si_src, si_x, si_y, bar, si_pol);
            } else {
                asm volatile("fence.proxy.async.global;" ::: "memory");
                bulk_load(si_dst, si_src, TILE_BYTES, bar, si_pol);
            }
        }
        __syncwarp();
    }
    __device__ __forceinline__ void a_tile(const Params& p, int row0, int n) {
        const int st = n % ASTAGES;
        if (lane == 0) mbar_expect_tx(mb(MB_AFULL + st), 32768);
        __syncwarp();
        if (lane < 8) tma2d_hint(sbase + st * 32768 + lane * 4096, &p.tm[6], lane * 64, row0 + n * (32 * SPLIT), mb(MB_AFULL + st), pol);
        __syncwarp();
    }
};

__device__ __forceinline__ void first_load(const Params& p, uint32_t sbase, unsigned blk) {
    const uint32_t bar = sbase + OFF_BAR + MB_FULL * 8;
    mbar_init(bar, 1);
    if (blk % APER != APER - 1) {
        const unsigned c = blk - blk / APER;
        fence_mbar_init();
        mbar_expect_tx(bar, TILE_BYTES);
        bulk_load(sbase + OFF_RING, (const char*)p.K + chunk_off(c), TILE_BYTES, bar, policy_evict_first());
    }
}
__device__ __forceinline__ void next_loads(const Params& p, uint32_t sbase, int vid) {
    const uint32_t bars = sbase + OFF_BAR;
    const uint64_t pol = policy_evict_first();
#pragma unroll
    for (int i = 0; i < MB_EARLY; i++) mbar_init(bars + i * 8, 1);
    fence_mbar_init();
    if (vid >= 0) {
#pragma unroll
        for (int q = 0; q < 4; q++) {
            mbar_expect_tx(bars + (MB_SIDE + q) * 8, TILE_BYTES);
            tma2d_hint(sbase + BLK_W + q * 16384, &p.tm[vid & 1], 64 * (vid >> 1), 128 * q, bars + (MB_SIDE + q) * 8, pol);
            if (q == 0) {
                mbar_expect_tx(bars + MB_X * 8, 4096);
                bulk_load_nohint(sbase + OFF_X, (vid & 1) ? p.xA : p.xB, 4096, bars + MB_X * 8);
            }
        }
    }
}

__device__ __forceinline__ void produce(const Params& p, char* smem, int lane, bool isA, int wk, int vid, int row0) {
    Producer pr;
    pr.sbase = smem_u32(smem);
    pr.lane = lane;
    pr.pol = policy_evict_first();
    pr.pend = !isA && lane < 5;
    pr.wbar = pr.mb(lane == 0 ? MB_FULL : MB_SIDE + lane - 1);
    pr.wpar = 0;
    pr.setup_side(p, vid);
    const int i0 = isA ? 8 * R_JOIN : 0;
    int i = isA ? i0 : 1, i_end = isA ? i0 : I_LAST, s = i - i0, ph = 0;
    int chunk = chunk_of(i >> 3, wk, vid);
    const char* src = (const char*)p.K + chunk_off(chunk) + (i & 3) * CHUNK_STEP;
    int nx = SI_WUK, nx_end = vid < 0 ? 0 : isA || (vid & 1) ? SI_WE : SI_WO;
    uint32_t gate = pr.mb(MB_X);
    int gmin = 0;
    bool last_tile = false;
#pragma unroll 1
    for (int phase = 0; phase < 3; phase++) {
#pragma unroll 1
        while (i < i_end || nx < nx_end) {
            if (nx < nx_end && i >= gmin) {
                bool side = true;
                if (i == i_end) mbar_wait(gate, 0);
                else side = __all_sync(0xffffffffu, mbar_test(gate, 0) &&
                                       (last_tile || (i - i0 >= NS && !mbar_test(pr.mb(MB_EMPTY + s), ph ^ 1))));
                if (side) {
                    last_tile = false;
                    pr.side(p, nx);
                    PROF2(160 + nx);
                    nx++;
                    gate = __shfl_sync(0xffffffffu, pr.si_gate, nx);
                    gmin = __shfl_sync(0xffffffffu, pr.si_min, nx);
                    continue;
                }
            }
            last_tile = true;
            const uint32_t full = pr.mb(MB_FULL + s);
            mbar_wait(pr.mb(MB_EMPTY + s), ph ^ 1);
            if (elect_one()) mbar_expect_tx(full, TILE_BYTES);
            pr.window(p, i, full, ph);
            if (elect_one()) bulk_load(pr.sbase + OFF_RING + s * TILE_BYTES, src, TILE_BYTES, full, pr.pol);
            PROF2(i);
            src += CHUNK_STEP;
            if ((++i & 3) == 0) {
                if ((i & 4) == 0) chunk = chunk_of(i >> 3, wk, vid);
                src = (const char*)((i & 4) ? p.V : p.K) + chunk_off(chunk);
            }
            if (++s == NS) { s = 0; ph ^= 1; }
        }
        if (!isA || phase == 2) break;
        if (phase == 0) {
#pragma unroll 1
            for (int k = -ASTAGES; k < ATILES; k++) {
                if (k == 3 - ASTAGES && vid >= 0) mbar_wait(pr.mb(MB_FU), 0);
                if (k >= 0) bar_sync(BAR_R, 352);
                const int n = k < 0 ? k + ASTAGES : k - 2 + ASTAGES;
                if ((k < 0 || k >= 2) && n < ATILES) { pr.a_tile(p, row0, n); PROF2(32 + n); }
            }
            mbar_wait(pr.mb(MB_F3), 0);
            if (vid >= 0 && !(vid & 1)) nx_end = SI_WO;
        } else {
            for (int k = 0; k < 500 && !__any_sync(0xffffffffu, pr.due(p, i0, lds_volatile2(pr.sbase + OFF_WIN))); k++) __nanosleep(100);
            i_end = vid >= 0 ? I_LAST : 8 * R_LATE;
        }
    }
    if (vid < 0) return;
#pragma unroll 1
    for (int u = 0; u < 4; u++) {
        const uint32_t full = pr.mb(MB_FULL + u);
        mbar_wait(pr.mb(MB_EMPTY + u), 1);
        if (elect_one()) mbar_expect_tx(full, TILE_BYTES);
        pr.window(p, I_LAST + u, full, 0);
        if (elect_one()) {
#pragma unroll
            for (int hf = 0; hf < 2; hf++)
                tma2d_hint(pr.sbase + OFF_RING + u * TILE_BYTES + hf * 8192, &p.tm[7], 64 * hf, (chunk_off(chunk) + u * CHUNK_STEP) / 256,
                           full, pr.pol);
        }
        PROF2(I_LAST + u);
    }
    mbar_wait(pr.mb((vid & 1) ? MB_F0 : MB_F2), 0);
#pragma unroll 1
    for (int u = 0; u < 4; u++) {
        const uint32_t bar = pr.mb(MB_SIDE + SI_WO + u);
        if (elect_one()) {
            mbar_expect_tx(bar, u < 3 ? TILE_BYTES : TILE_BYTES / 2);
            if (u == 3) mbar_expect_tx(bar + 8, TILE_BYTES / 2);
        }
        pr.window(p, I_BOX + u, bar, 0);
        if (elect_one()) {
#pragma unroll
            for (int k = 0; k < 2; k++)
                tma2d_hint(pr.sbase + BLK_W + u * TILE_BYTES + k * (TILE_BYTES / 2), &p.tm[2 + (vid & 1)], 64 * ((vid >> 1) & 7),
                           1024 * u + 128 * (vid >> 4) + 64 * k, bar + (u == 3 ? 8 * k : 0), pr.pol);
        }
        PROF2(I_BOX + u);
    }
}

__device__ __forceinline__ void consume(const Params& p, char* smem, bool isA, int wk, int vid, int w, int lane) {
    const uint32_t sbase = smem_u32(smem);
    const uint32_t bars = sbase + OFF_BAR;
    const int g = lane >> 2, t = lane & 3;
    const int mat = lane >> 3, r8 = lane & 7;
    const uint32_t kbase = sbase + OFF_RING + (r8 + 8 * (mat & 1)) * 256 + (mat >> 1) * 128 + r8 * 16;
    const uint32_t vbase = sbase + OFF_RING + (r8 + 8 * (mat >> 1)) * 256 + (mat & 1) * 128 + r8 * 16;
    uint32_t mask[8];
#pragma unroll
    for (int c = 0; c < 8; c++) mask[c] = pv_mask(c, g, t);
    uint32_t* qtab = (uint32_t*)(smem + OFF_Q);
    if (!isA) {
        mbar_wait(bars + MB_F0 * 8, 0);
        __nanosleep(TUNED(QSLEEP));
        const unsigned* src = p.sc->qB + (chunk_of(0, wk, vid) >> 4) * 64 + lane;
        unsigned q0, q1, spins = 0;
        while (true) {
            q0 = ll_load(src);
            q1 = ll_load(src + 32);
            if (q0 && q1) break;
            __nanosleep(200);
            if (++spins > SPIN_LIMIT) __trap();
        }
        qtab[lane] = ~q0;
        qtab[32 + lane] = ~q1;
        __syncwarp();
        if (w == 0) PROF(1);
    }
    const int r_end = vid >= 0 ? R_LATE + 1 : R_LATE;
    int s = w, ph = 0;
    int done = 0;
#pragma unroll 1
    for (int r = isA ? R_JOIN : 0; r < r_end; r++) {
        const int chunk = chunk_of(r, wk, vid);
        if (r >= 1) mbar_wait(bars + MB_Q * 8, 0);
        uint32_t qf[8][2];
#pragma unroll
        for (int c = 0; c < 8; c++) {
            qf[c][0] = qtab[r * 64 + (c ^ g) * 4 + t];
            qf[c][1] = qtab[r * 64 + 32 + (c ^ g) * 4 + t];
        }
        uint32_t pf[2][4][2];
        float m[2], l[2];
#pragma unroll
        for (int u = 0; u < 2; u++) {
            mbar_wait(bars + (MB_FULL + s) * 8, ph);
            done++;
            float acc[4][4];
#pragma unroll
            for (int gr = 0; gr < 4; gr++) zero4(acc[gr]);
#pragma unroll
            for (int c = 0; c < 8; c++) {
#pragma unroll
                for (int gr = 0; gr < 4; gr++) {
                    uint32_t a0, a1, a2, a3;
                    ldsm4(a0, a1, a2, a3, (kbase ^ (c << 4)) + s * TILE_BYTES + gr * 4096);
                    mma(acc[gr], a0, a1, a2, a3, qf[c][0], qf[c][1]);
                }
            }
            warp_release(bars + (MB_EMPTY + s) * 8, lane, (acc[0][0] + acc[1][0]) + (acc[2][0] + acc[3][0]));
#pragma unroll
            for (int gr = 0; gr < 4; gr++) {
                const uint32_t su = score_round2((g & 1) ? acc[gr][1] : acc[gr][0], (g & 1) ? acc[gr][3] : acc[gr][2]);
                const uint32_t x = __shfl_sync(0xffffffffu, su, 9 * t), y = __shfl_sync(0xffffffffu, su, 9 * t + 4);
                pf[u][gr][0] = __byte_perm(x, y, 0x5410);
                pf[u][gr][1] = __byte_perm(x, y, 0x7632);
            }
            m[u] = -INFINITY;
            l[u] = 0.f;
#pragma unroll
            for (int k = 0; k < 8; k++) m[u] = fmaxf(m[u], fmaxf(bf_lo(pf[u][k >> 1][k & 1]), bf_hi(pf[u][k >> 1][k & 1])));
            m[u] = fmaxf(m[u], __shfl_xor_sync(0xffffffffu, m[u], 1));
            m[u] = fmaxf(m[u], __shfl_xor_sync(0xffffffffu, m[u], 2));
#pragma unroll
            for (int k = 0; k < 8; k++) {
                uint32_t& x = pf[u][k >> 1][k & 1];
                const float e0 = ex2((bf_lo(x) - m[u]) * LOG2E), e1 = ex2((bf_hi(x) - m[u]) * LOG2E);
                l[u] += e0 + e1;
                x = pack_bf16(e0, e1);
            }
            l[u] += __shfl_xor_sync(0xffffffffu, l[u], 1);
            l[u] += __shfl_xor_sync(0xffffffffu, l[u], 2);
            if (lane == 0) sts_volatile(sbase + OFF_DONE + 4 * w, done);
            if (r == R_LATE) {
                if (lane < 4) {
                    uint4* dst = (uint4*)(smem + OFF_PH + (2 * u + w) * 128 + t * 32);
                    dst[0] = make_uint4(pf[u][0][0], pf[u][0][1], pf[u][1][0], pf[u][1][1]);
                    dst[1] = make_uint4(pf[u][2][0], pf[u][2][1], pf[u][3][0], pf[u][3][1]);
                    if (lane == 0) ((float2*)(smem + OFF_MLO))[2 * u + w] = make_float2(m[u], l[u]);
                }
                __syncwarp();
                if (lane == 0) mbar_expect_tx(bars + MB_PH * 8, 0);
            }
            if ((s += 2) >= NS) { s -= NS; ph ^= 1; }
        }
        if (r == R_LATE) break;
        const float mw = fmaxf(m[0], m[1]);
        float o[4] = {0.f, 0.f, 0.f, 0.f}, lw = 0.f;
#pragma unroll
        for (int u = 0; u < 2; u++) {
            const float a = ex2((m[u] - mw) * LOG2E);
            lw = fmaf(a, l[u], lw);
            float oacc[4][4];
#pragma unroll
            for (int gr = 0; gr < 4; gr++) zero4(oacc[gr]);
            mbar_wait(bars + (MB_FULL + s) * 8, ph);
            PROF(u ? 2 + w : 19 + w);
            done++;
#pragma unroll
            for (int c = 0; c < 8; c++) {
#pragma unroll
                for (int gr = 0; gr < 4; gr++) {
                    uint32_t a0, a1, a2, a3;
                    ldsm4t(a0, a1, a2, a3, (vbase ^ (c << 4)) + s * TILE_BYTES + gr * 4096);
                    mma(oacc[gr], a0, a1, a2, a3, pf[u][gr][0] & mask[c], pf[u][gr][1] & mask[c]);
                }
            }
#pragma unroll
            for (int e = 0; e < 4; e++) o[e] = fmaf(a, (oacc[0][e] + oacc[1][e]) + (oacc[2][e] + oacc[3][e]), o[e]);
            warp_release(bars + (MB_EMPTY + s) * 8, lane, o[0]);
            if (lane == 0) sts_volatile(sbase + OFF_DONE + 4 * w, done);
            if ((s += 2) >= NS) { s -= NS; ph ^= 1; }
        }
        float4* op = (float4*)(smem + OFF_OPART) + (r & 1) * 32 + lane;
        float2* ml = (float2*)(smem + OFF_ML) + (r & 1);
        if (w == 0) {
            *op = make_float4(o[0], o[1], o[2], o[3]);
            if (lane == 0) *ml = make_float2(mw, lw);
            bar_arrive(BAR_B + (r & 1), 64);
        } else {
            bar_sync(BAR_B + (r & 1), 64);
            const float2 ot = *ml;
            const float4 oo = *op;
            const float M = fmaxf(mw, ot.x), a = ex2((mw - M) * LOG2E), b = ex2((ot.x - M) * LOG2E);
            ll_store4(p.sc->part + chunk * 128 + lane * 4, a * o[0] + b * oo.x, a * o[1] + b * oo.y,
                      a * o[2] + b * oo.z, a * o[3] + b * oo.w);
            if (lane == 0) ll_store2(p.sc->pml + chunk * 2, __float_as_uint(M), __float_as_uint(a * lw + b * ot.y));
            PROF(10);
        }
    }
}

__device__ __forceinline__ uint2 merge_chunks(const Params& p, int pair, int lane) {
    Scratch* sc = p.sc;
    const unsigned* pm = sc->pml + pair * 32 + 2 * (lane & 15);
    const unsigned* base = sc->part + pair * 2048 + 4 * lane;
    unsigned um = 0, ul = 0;
    uint4 u[16];
#pragma unroll
    for (int c = 0; c < 16; c++) u[c] = make_uint4(0, 0, 0, 0);
    for (unsigned spins = 0;; spins++) {
        if (!(um && ul)) { um = ll_load(pm); ul = ll_load(pm + 1); }
#pragma unroll
        for (int c = 0; c < 16; c++)
            if (!ll_ok4(u[c])) u[c] = ll_load4(base + c * 128);
        bool ok = um && ul;
#pragma unroll
        for (int c = 0; c < 16; c++) ok &= ll_ok4(u[c]);
        if (__all_sync(0xffffffffu, ok)) break;
        __nanosleep(100);
        if (spins > SPIN_LIMIT) __trap();
    }
    const float m = __uint_as_float(~um);
    const float M = redux_max(m);
    const float wgt = ex2((m - M) * LOG2E);
    float l = wgt * __uint_as_float(~ul);
#pragma unroll
    for (int k = 8; k > 0; k >>= 1) l += __shfl_xor_sync(0xffffffffu, l, k);
    float o[4] = {0.f, 0.f, 0.f, 0.f};
#pragma unroll
    for (int c = 0; c < 16; c++) {
        const float wc = __shfl_sync(0xffffffffu, wgt, c);
        o[0] = fmaf(wc, __uint_as_float(~u[c].x), o[0]); o[1] = fmaf(wc, __uint_as_float(~u[c].y), o[1]);
        o[2] = fmaf(wc, __uint_as_float(~u[c].z), o[2]); o[3] = fmaf(wc, __uint_as_float(~u[c].w), o[3]);
    }
    const float inv = __frcp_rn(l);
    const uint32_t lo = pack_bf16(o[0] * inv, o[2] * inv), hi = pack_bf16(o[1] * inv, o[3] * inv);
    const bool odd = lane & 4;
    const uint32_t x = __shfl_xor_sync(0xffffffffu, odd ? lo : hi, 4), a = odd ? x : lo, b = odd ? hi : x;
    return make_uint2(__byte_perm(a, b, 0x5410), __byte_perm(a, b, 0x7632));
}

__device__ __forceinline__ int qabs_word(int b, int h, int j, int ks, int nt, int t) {
    return b * 8192 + (((h >> 4) + 2 * j) * 8 + ks) * 128 + ((h & 7) * 4 + t) * 4 + ((h >> 3) & 1) + 2 * nt;
}
__device__ __forceinline__ void service(const Params& p, char* smem, bool isA, int vid, int lane) {
    const uint32_t sbase = smem_u32(smem);
    const int i0 = isA ? 8 * R_JOIN : 0, stop = vid >= 0 ? I_BOX : 8 * R_LATE;
    const int c = 16 * vid + 15;
    const int rl = c < R_JOIN * NB ? c / NB : R_JOIN + (c - R_JOIN * NB) / NCTA;
    const int due = 8 * (rl + 1) + (rl + 1 == R_LATE ? TUNED(MERGE) : TUNED(MERGE0));
    const int ow = 8 * (lane & 3) + (lane & 4) + (lane >> 3);
    bool merged = vid < 0 || vid >= N_EARLY, counted = vid < 0;
    int last = i0, z = 0;
    unsigned t0 = clock(), t1 = t0, prev = 0;
    if (isA) mbar_wait(sbase + OFF_BAR + MB_F3 * 8, 0);
    for (unsigned spins = 0; last < stop || !counted || !merged; spins++) {
        const int pos = __shfl_sync(0xffffffffu, i0 + lds_volatile(sbase + OFF_DONE) + lds_volatile(sbase + OFF_DONE + 4), 0);
        if (!merged && pos > due) {
            const int pair = vid;
            const uint2 o = merge_chunks(p, pair, lane);
            ll_store(p.sc->oB + pair * 64 + ow, o.x);
            ll_store(p.sc->oB + pair * 64 + ow + 32, o.y);
#pragma unroll
            for (int k = 0; k < 16; k++) *(uint4*)(p.sc->part + pair * 2048 + k * 128 + 4 * lane) = make_uint4(0, 0, 0, 0);
            p.sc->pml[pair * 32 + lane] = 0;
            *(uint2*)(p.sc->qB + pair * 64 + 2 * lane) = make_uint2(0, 0);
            PROF(12);
            merged = true;
            continue;
        }
        const unsigned now = __shfl_sync(0xffffffffu, (unsigned)clock(), 0);
        const bool look = pos > last || (isA && pos == i0 && now - t1 > 2000);
        unsigned old = 0;
        if (look && lane == 0) old = pos > last ? atomicAdd(&p.sc->prog, pos - last) : ll_load(&p.sc->prog);
        if (!counted && now - t0 > 2000 && (isA || pos > TUNED(CNT0))) {
            t0 = now;
            if (__all_sync(0xffffffffu, ld_acquire(&p.sc->cnt) >= 4 * SPLIT)) {
                if (lane == 0) {
                    mbar_expect_tx(sbase + OFF_BAR + MB_CNT * 8, 0);
                    bump_counter(&p.sc->cnt);
                }
                *(uint2*)(p.sc->qA + vid * 64 + lane * 2) = make_uint2(0, 0);
                *(uint4*)(p.sc->qabs + vid * 256 + lane * 4) = make_uint4(0, 0, 0, 0);
                *(uint4*)(p.sc->qabs + vid * 256 + 128 + lane * 4) = make_uint4(0, 0, 0, 0);
                counted = true;
            }
        }
        if (look) {
            if (lane == 0) {
                if (pos > last && old + (pos - last) == tiles4(4 * I_BOX) / 4) p.sc->prog = 0;
                if (old > prev && old >= 6 * NB && old < tiles4(4 * I_BOX - 8) / 4) {
                    const int zn = clock_after(old) - old * TUNED(TAU) / 128 + ((vid >> 4) & 7) * TUNED(STAG);
                    z = prev && zn - z < TUNED(JUMP) ? z + ((zn - z) >> TUNED(GAIN)) : zn;
                    prev = old;
                    sts_volatile2(sbase + OFF_WIN, 4 * old < tiles4(4 * TUNED(IMIN)) ? TUNED(WMIN0) : TUNED(WMIN), z);
                }
            }
            t1 = now;
        } else {
            __nanosleep(TUNED(SVC));
        }
        last = pos;
        if (spins > SPIN_LIMIT) __trap();
    }
}

__device__ __forceinline__ void softmax_A(const Params& p, char* smem, int w, int lane, int ab, int asp) {
    const int mat = lane >> 3, r = lane & 7;
    float m_run[4], l_run[4];
#pragma unroll
    for (int i = 0; i < 4; i++) { m_run[i] = -INFINITY; l_run[i] = 0.f; }
    const float* red = (const float*)(smem + OFF_ARED);
    for (int k = 0; k < ATILES; k++) {
        bar_sync(BAR_R, 352);
        float4 s[4];
        float mt[4];
#pragma unroll
        for (int i = 0; i < 4; i++) {
            const float* src = red + (16 * w + 4 * i + mat) * 40 + 4 * r;
            const float4 a = *(const float4*)src, b = *(const float4*)(src + 32 * 40);
            const float4 c = *(const float4*)(src + 64 * 40), d = *(const float4*)(src + 96 * 40);
            const uint32_t v0 = score_round2((a.x + b.x) + (c.x + d.x), (a.y + b.y) + (c.y + d.y));
            const uint32_t v1 = score_round2((a.z + b.z) + (c.z + d.z), (a.w + b.w) + (c.w + d.w));
            s[i] = make_float4(bf_lo(v0), bf_hi(v0), bf_lo(v1), bf_hi(v1));
            mt[i] = fmaxf(fmaxf(s[i].x, s[i].y), fmaxf(s[i].z, s[i].w));
        }
#pragma unroll
        for (int o = 1; o < 8; o <<= 1)
#pragma unroll
            for (int i = 0; i < 4; i++) mt[i] = fmaxf(mt[i], __shfl_xor_sync(0xffffffffu, mt[i], o));
#pragma unroll
        for (int i = 0; i < 4; i++) {
            const int head = 16 * w + 4 * i + mat;
            const float m_new = fmaxf(m_run[i], mt[i]);
            const float al = ex2((m_run[i] - m_new) * LOG2E);
            const float e0 = ex2((s[i].x - m_new) * LOG2E), e1 = ex2((s[i].y - m_new) * LOG2E);
            const float e2 = ex2((s[i].z - m_new) * LOG2E), e3 = ex2((s[i].w - m_new) * LOG2E);
            l_run[i] = l_run[i] * al + (e0 + e1) + (e2 + e3);
            m_run[i] = m_new;
            *(uint2*)(smem + OFF_AP + (k & 1) * 2560 + head * 80 + r * 8) = make_uint2(pack_bf16(e0, e1), pack_bf16(e2, e3));
            if (r == 0) ((float*)(smem + OFF_AALPHA))[(k & 1) * 32 + head] = al;
        }
        bar_arrive(BAR_P, 320);
    }
#pragma unroll
    for (int i = 0; i < 4; i++) {
        float l = l_run[i];
        l += __shfl_xor_sync(0xffffffffu, l, 1);
        l += __shfl_xor_sync(0xffffffffu, l, 2);
        l += __shfl_xor_sync(0xffffffffu, l, 4);
        if (r == 0) p.sc->ml[((16 * w + 4 * i + mat) * SPLIT + asp) * 4 + ab] = make_float2(m_run[i], l);
    }
    bar_arrive(BAR_E, 320);
}

__device__ __forceinline__ void attention_A(const Params& p, char* smem, int sw, int lane, int ab, int asp, bool idle_before) {
    const uint32_t sbase = smem_u32(smem);
    const int tid = sw * 32 + lane;
    const int g = lane >> 2, t = lane & 3, mat = lane >> 3, r = lane & 7;
    const int mi = sw & 1, cq = sw >> 1;
    uint4 qf[8];
    {
        const unsigned* src = p.sc->qabs + ab * 8192 + sw * 1024 + lane * 4;
        for (int k = 0; k < (idle_before ? TUNED(ASLEEP) : TUNED(ASLEEP2)); k++) __nanosleep(1000);
        ll_poll4(qf, src, 128, 500);
        if (sw == 0) PROF(6);
    }
    bar_sync(BAR_S, NSW * 32);
    float oacc[2][8][4];
#pragma unroll
    for (int a = 0; a < 2; a++)
#pragma unroll
        for (int b = 0; b < 8; b++) zero4(oacc[a][b]);
    float* red = (float*)(smem + OFF_ARED) + (cq * 32 + 16 * mi + g) * 40 + 2 * t;
    const uint32_t qk_off = sbase + 2 * cq * 4096 + ((mat >> 1) * 8 + r) * 128 + (((mat & 1) ^ r) << 4);
    const uint32_t pv_off = sbase + sw * 4096 + ((mat & 1) * 8 + r) * 128 + (((mat >> 1) ^ r) << 4);
    const uint32_t p_off = sbase + OFF_AP + ((mat & 1) * 8 + r) * 80 + (mat >> 1) * 16;
    int st = 0, ph = 0, stp = 0;
    for (int k = -1; k < ATILES; k++) {
        float sacc[4][4];
        if (k + 1 < ATILES) {
            mbar_wait(sbase + OFF_BAR + (MB_AFULL + st) * 8, ph);
            if (k == -1 && sw == 0) PROF(13);
#pragma unroll
            for (int a = 0; a < 4; a++) zero4(sacc[a]);
#pragma unroll
            for (int ks = 0; ks < 8; ks++) {
#pragma unroll
                for (int np = 0; np < 2; np++) {
                    uint32_t b0, b1, b2, b3;
                    ldsm4(b0, b1, b2, b3, (qk_off ^ ((ks & 3) << 5)) + st * 32768 + (ks >> 2) * 4096 + np * 2048);
                    mma(sacc[2 * np], qf[ks].x, qf[ks].y, qf[ks].z, qf[ks].w, b0, b1);
                    mma(sacc[2 * np + 1], qf[ks].x, qf[ks].y, qf[ks].z, qf[ks].w, b2, b3);
                }
            }
        }
        if (k >= 0) bar_sync(BAR_P, 320);
        if (k + 1 < ATILES) {
#pragma unroll
            for (int nt = 0; nt < 4; nt++) {
                *(float2*)(red + 8 * nt) = make_float2(sacc[nt][0], sacc[nt][1]);
                *(float2*)(red + 8 * nt + 8 * 40) = make_float2(sacc[nt][2], sacc[nt][3]);
            }
            bar_arrive(BAR_R, 352);
        }
        if (k >= 0) {
            const float* alpha = (const float*)(smem + OFF_AALPHA) + (k & 1) * 32;
            const float al0 = alpha[g], al1 = alpha[g + 8], al2 = alpha[g + 16], al3 = alpha[g + 24];
            if (!__all_sync(0xffffffffu, al0 == 1.f && al1 == 1.f && al2 == 1.f && al3 == 1.f)) {
#pragma unroll
                for (int nt = 0; nt < 8; nt++) {
                    oacc[0][nt][0] *= al0; oacc[0][nt][1] *= al0; oacc[0][nt][2] *= al1; oacc[0][nt][3] *= al1;
                    oacc[1][nt][0] *= al2; oacc[1][nt][1] *= al2; oacc[1][nt][2] *= al3; oacc[1][nt][3] *= al3;
                }
            }
#pragma unroll
            for (int ks = 0; ks < 2; ks++) {
                uint32_t pa[2][4];
#pragma unroll
                for (int mt = 0; mt < 2; mt++)
                    ldsm4(pa[mt][0], pa[mt][1], pa[mt][2], pa[mt][3], p_off + (k & 1) * 2560 + mt * 16 * 80 + ks * 32);
#pragma unroll
                for (int np = 0; np < 4; np++) {
                    uint32_t b0, b1, b2, b3;
                    ldsm4t(b0, b1, b2, b3, (pv_off ^ (np << 5)) + stp * 32768 + ks * 2048);
#pragma unroll
                    for (int mt = 0; mt < 2; mt++) {
                        mma(oacc[mt][2 * np], pa[mt][0], pa[mt][1], pa[mt][2], pa[mt][3], b0, b1);
                        mma(oacc[mt][2 * np + 1], pa[mt][0], pa[mt][1], pa[mt][2], pa[mt][3], b2, b3);
                    }
                }
            }
        }
        stp = st;
        if (++st == ASTAGES) { st = 0; ph ^= 1; }
    }
    if (sw == 0) PROF(14);
    {
        float dep = 0.f;
#pragma unroll
        for (int nt = 0; nt < 8; nt++) dep += oacc[1][nt][0];
        warp_release(sbase + OFF_BAR + MB_F3 * 8, lane, dep);
    }
#pragma unroll
    for (int mt = 0; mt < 2; mt++)
#pragma unroll
        for (int hh = 0; hh < 2; hh++) {
            float4* op = (float4*)(p.sc->opart + ((16 * mt + 8 * hh + g) * SPLIT + asp) * 2048 + sw * 256 + ab * 64) + t;
#pragma unroll
            for (int q = 0; q < 4; q++)
                op[4 * q] = make_float4(oacc[mt][2 * q][2 * hh], oacc[mt][2 * q][2 * hh + 1],
                                    oacc[mt][2 * q + 1][2 * hh], oacc[mt][2 * q + 1][2 * hh + 1]);
        }
    bar_sync(BAR_E, 320);
    if (tid == 0) signal_counter(&p.sc->cnt);
    if (sw == 0) PROF(7);
}

__device__ __forceinline__ float matvec64(char* smem, const uint32_t (&xf)[4][2], int mb_full, int mb_free, int sw, int lane) {
    const uint32_t sbase = smem_u32(smem);
    const int g = lane >> 2, t = lane & 3, mat = lane >> 3, r = lane & 7;
    const uint32_t a = sbase + BLK_W + sw * 8192 + ((mat >> 1) * 8 + r) * 128 + (((mat & 1) ^ r) << 4);
    float c[4][4];
#pragma unroll
    for (int mt = 0; mt < 4; mt++) zero4(c[mt]);
    mbar_wait(sbase + OFF_BAR + (mb_full + (sw >> 1)) * 8, 0);
#pragma unroll
    for (int ks = 0; ks < 4; ks++)
#pragma unroll
        for (int mt = 0; mt < 4; mt++) {
            uint32_t a0, a1, a2, a3;
            ldsm4t(a0, a1, a2, a3, (a ^ (mt << 5)) + ks * 2048);
            mma(c[mt], a0, a1, a2, a3, xf[ks][0], xf[ks][1]);
        }
    warp_release(sbase + OFF_BAR + mb_free * 8, lane, (c[0][0] + c[1][0]) + (c[2][0] + c[3][0]));
    float* rp = (float*)(smem + OFF_RED);
#pragma unroll
    for (int mt = 0; mt < 4; mt++) {
        const float y0 = (t < 2 ? c[mt][0] : c[mt][2]) + __shfl_xor_sync(0xffffffffu, t < 2 ? c[mt][2] : c[mt][0], 2);
        const float y1 = (t < 2 ? c[mt][1] : c[mt][3]) + __shfl_xor_sync(0xffffffffu, t < 2 ? c[mt][3] : c[mt][1], 2);
        float* d = rp + sw * 256 + (t & 1) * 128 + 16 * mt + (t >> 1) * 8 + g;
        d[0] = y0;
        d[64] = y1;
    }
    bar_sync(BAR_S, NSW * 32);
    float y = 0.f;
#pragma unroll
    for (int i = 0; i < NSW; i++) y += rp[i * 256 + sw * 32 + lane];
    return y;
}
__device__ __forceinline__ void load_xfrags(const char* smem, uint32_t (&xf)[4][2], int sw, int lane) {
    const uint32_t* x32 = (const uint32_t*)(smem + OFF_X) + ((lane >> 2) & 3) * 256 + 32 * sw + (lane & 3);
#pragma unroll
    for (int ks = 0; ks < 4; ks++) {
        xf[ks][0] = lane < 16 ? x32[ks * 8] : 0u;
        xf[ks][1] = lane < 16 ? x32[ks * 8 + 4] : 0u;
    }
}
__device__ __forceinline__ int vec_word(int vid, int tid) { return (tid >> 6) * 2048 + (vid >> 1) * 32 + ((tid & 63) >> 1); }
__device__ __forceinline__ void store_vec(unsigned* dst, int vid, int tid, float y) {
    const float y1 = __shfl_down_sync(0xffffffffu, y, 1);
    if (!(tid & 1)) ll_store(dst + vec_word(vid, tid), pack_bf16(y, y1));
}
__device__ __forceinline__ void fill_qtab(const Params& p, char* smem, bool isA, int wk, int vid, int tid) {
    const int r = 1 + (tid >> 4);
    uint4 v[1];
    const bool used = (!isA || r >= R_JOIN) && (vid >= 0 || r < R_LATE);
    const int pair = chunk_of(used ? r : R_JOIN, wk, vid) >> 4;
    ll_poll4(v, p.sc->qB + pair * 64 + (tid & 15) * 4, 0, 300);
    *(uint4*)(smem + OFF_Q + 256 + tid * 16) = v[0];
    __syncwarp();
    if ((tid & 31) == 0) mbar_expect_tx(smem_u32(smem) + OFF_BAR + MB_Q * 8, 0);
}
__device__ __forceinline__ void clear_handoffs(const Params& p, int vid, int tid) {
    const int chunk = chunk_of(R_LATE, 0, vid);
    if (tid < 32) *(uint4*)(p.sc->part + chunk * 128 + tid * 4) = make_uint4(0, 0, 0, 0);
    if (tid == 32) *(uint2*)(p.sc->pml + chunk * 2) = make_uint2(0, 0);
    if ((tid >> 4) == 4 && vid < N_EARLY) *(uint4*)(p.sc->oB + vid * 64 + (tid & 15) * 4) = make_uint4(0, 0, 0, 0);
    if ((tid >> 2) == 24) *(uint4*)(p.out + vid * 32 + (tid & 3) * 8) = make_uint4(0, 0, 0, 0);
    if (!((vid | tid) & 1)) p.sc->ctx[vec_word(vid, tid)] = 0;
}
__device__ __forceinline__ void side_prologue(const Params& p, char* smem, bool isA, int wk, int vid, int sw, int lane) {
    const uint32_t sbase = smem_u32(smem);
    const uint32_t bars = sbase + OFF_BAR;
    const int h = vid & 31, j = vid >> 5;
    const int tid = sw * 32 + lane;
    const int g = lane >> 2, t = lane & 3, mat = lane >> 3, r = lane & 7;
    {
        uint32_t xf[4][2];
        mbar_wait(bars + MB_X * 8, 0);
        load_xfrags(smem, xf, sw, lane);
        if (sw == 0) PROF(16);
        store_vec((vid & 1) ? p.sc->qA : p.sc->qB, vid, tid, matvec64(smem, xf, MB_SIDE + SI_WQ, MB_F0, sw, lane));
        if (sw == 0) PROF(18);
    }
    if (tid == 255) asm volatile("fence.acq_rel.gpu;" ::: "memory");
    __syncwarp();
    __nanosleep(TUNED(GSLEEP));
    if (tid < 64) {
        uint4 v[1];
        ll_poll4(v, p.sc->qA + (tid >> 4) * 2048 + h * 64 + (tid & 15) * 4, 0, 300);
        *(uint4*)(smem + OFF_VEC + (tid >> 4) * 272 + (tid & 15) * 16) = v[0];
    }
    fill_qtab(p, smem, isA, wk, vid, tid);
    bar_sync(BAR_S, NSW * 32);
    if (sw == 0) PROF(21);
    {
        mbar_wait(bars + (MB_SIDE + SI_WUK) * 8, 0);
        mbar_wait(bars + (MB_SIDE + SI_WUK + 1) * 8, 0);
        float c2[2][4];
        zero4(c2[0]); zero4(c2[1]);
        const uint32_t* qa = (const uint32_t*)(smem + OFF_VEC + (g & 3) * 272) + t;
        const uint32_t a = sbase + BLK_U + sw * 2048 + ((mat >> 1) * 8 + r) * 128 + (((mat & 1) ^ r) << 4);
#pragma unroll
        for (int ks = 0; ks < 8; ks++) {
            uint32_t b0, b1, b2, b3;
            ldsm4(b0, b1, b2, b3, (a ^ ((ks & 3) << 5)) + (ks >> 2) * 16384);
            const uint32_t a0 = qa[ks * 8], a2 = qa[ks * 8 + 4];
            mma(c2[0], a0, 0, a2, 0, b0, b1);
            mma(c2[1], a0, 0, a2, 0, b2, b3);
        }
        warp_release(bars + MB_FU * 8, lane, c2[0][0] + c2[1][0]);
        ll_store(p.sc->qabs + qabs_word(g & 3, h, j, sw, g >> 2, t),
                 g < 4 ? pack_bf16(c2[0][0], c2[0][1]) : pack_bf16(c2[1][0], c2[1][1]));
    }
    if (sw == 0) PROF(5);
}

__device__ __forceinline__ void side_epilogue(const Params& p, char* smem, int vid, int sw, int lane) {
    const uint32_t sbase = smem_u32(smem);
    const uint32_t bars = sbase + OFF_BAR;
    const int tid = sw * 32 + lane;
    const int g = lane >> 2, t = lane & 3;
    mbar_wait(bars + MB_CNT * 8, 0);
    if (sw == 0) PROF(8);
    if (!(vid & 1)) {
        uint32_t of[4][2];
        const int h = vid >> 2;
        const int b = g & 3, sp = g >> 2;
        float wgt[SPLIT / 2];
        {
            float2 ml[SPLIT / 2];
            float M = -INFINITY, L = 0.f;
#pragma unroll
            for (int q = 0; q < SPLIT / 2; q++) { ml[q] = __ldcg(&p.sc->ml[(h * SPLIT + sp + 2 * q) * 4 + b]); M = fmaxf(M, ml[q].x); }
            M = fmaxf(M, __shfl_xor_sync(0xffffffffu, M, 16));
#pragma unroll
            for (int q = 0; q < SPLIT / 2; q++) { wgt[q] = ex2((ml[q].x - M) * LOG2E); L = fmaf(wgt[q], ml[q].y, L); }
            L += __shfl_xor_sync(0xffffffffu, L, 16);
#pragma unroll
            for (int q = 0; q < SPLIT / 2; q++) { wgt[q] /= L; mbar_wait(bars + (MB_SIDE + SI_OPART + q) * 8, 0); }
        }
#pragma unroll
        for (int ks = 0; ks < 4; ks++) {
            float v[4] = {0.f, 0.f, 0.f, 0.f};
#pragma unroll
            for (int q = 0; q < SPLIT / 2; q++) {
                const float4 u = *((const float4*)(smem + BLK_U) + (sp + 2 * q) * 512 + sw * 64 + b * 16 + 4 * ks + t);
                v[0] = fmaf(u.x, wgt[q], v[0]); v[1] = fmaf(u.y, wgt[q], v[1]);
                v[2] = fmaf(u.z, wgt[q], v[2]); v[3] = fmaf(u.w, wgt[q], v[3]);
            }
#pragma unroll
            for (int e = 0; e < 4; e++) v[e] += __shfl_xor_sync(0xffffffffu, v[e], 16);
#pragma unroll
            for (int hh = 0; hh < 2; hh++) {
                const uint32_t hi = pack_bf16(v[2 * hh], v[2 * hh + 1]);
                of[ks][hh] = sp == 0 ? hi : pack_bf16(v[2 * hh] - bf_lo(hi), v[2 * hh + 1] - bf_hi(hi));
            }
        }
        store_vec(p.sc->ctx, vid, tid, matvec64(smem, of, MB_SIDE + SI_WE, MB_F2, sw, lane));
        if (sw == 0) PROF(9);
    }
    const bool isB = !(vid & 1), late = isB && tid >= 240;
    const unsigned* xs = (isB ? p.sc->oB : p.sc->ctx) + (tid >> 4) * 512 + (vid >> 4) * 64 + (tid & 15) * 4;
    const uint32_t xa = sbase + OFF_X + t * (4 * XROW) + (lane & 8) * 4 + (lane & 16);
    const uint32_t wa = sbase + BLK_W + lane * 128 + ((sw ^ (lane & 7)) << 4);
    const uint32_t va = sbase + OFF_RING + (sw >> 2) * 8192 + ((lane >> 4) * 8 + (lane & 7)) * 128 + (((2 * (sw & 3) + (g >> 1 & 1)) ^ (lane & 7)) << 4);
    uint32_t* out = (uint32_t*)(p.out + (g & 3) * 1024 + (isB ? 512 : 0) + ((vid >> 1) & 7) * 64 + 8 * sw) + t;
    unsigned* lp = p.sc->part + late_pair(vid) * 2048 + 16 * sw;
    unsigned* lm = p.sc->pml + late_pair(vid) * 32;
    const uint4* lf = (const uint4*)(smem + OFF_X + 4 * (3 * XROW + 192)) + t;
    __nv_bfloat16* lx = (__nv_bfloat16*)(smem + OFF_X) + 2 * (3 * XROW + 192) + 32 * (sw >> 1) + 16 * (t & 1) + ((lane & 16) >> 1) +
                        2 * (t & 2) + 2 * (sw & 1) + ((lane >> 3) & 1);
#pragma unroll 1
    for (int pass = 0; pass < 2; pass++) {
        const uint32_t wo = bars + (pass ? MB_SIDE + SI_WO : MB_X) * 8, vf = bars + (pass ? MB_FULL : MB_X) * 8;
        uint4 v = make_uint4(1, 1, 1, 1), u0 = v, u1 = v;
        uint2 m0 = make_uint2(1, 1), m1 = m0;
        {
            mbar_wait(bars + (pass ? MB_PH : MB_CNT) * 8, 0);
            const float4 ma = *(const float4*)(smem + OFF_MLO), mb = *(const float4*)(smem + OFF_MLO + 16);
            const float M = fmaxf(fmaxf(ma.x, ma.z), fmaxf(mb.x, mb.z));
            const float a[4] = {ex2((ma.x - M) * LOG2E), ex2((ma.z - M) * LOG2E), ex2((mb.x - M) * LOG2E), ex2((mb.z - M) * LOG2E)};
            if (pass && tid == 0)
                ll_store2(lm + 2 * (vid & 15), __float_as_uint(M), __float_as_uint((a[0] * ma.y + a[1] * ma.w) + (a[2] * mb.y + a[3] * mb.w)));
            const int done = lds_volatile(sbase + OFF_DONE);
            float f = 0.f;
#pragma unroll
            for (int u = 0; u < 4; u++) {
                const uint4 p0 = *(const uint4*)(smem + OFF_PH + u * 128 + t * 32), p1 = *(const uint4*)(smem + OFF_PH + u * 128 + t * 32 + 16);
                const uint32_t pb[4][2] = {{p0.x, p0.y}, {p0.z, p0.w}, {p1.x, p1.y}, {p1.z, p1.w}};
                float c[4][4];
                mbar_wait(vf + u * 8, 0);
                if (sw == 0) PROF(u < 2 ? 19 + u : u);
#pragma unroll
                for (int k = 0; k < 4; k++) {
                    uint32_t a0, a1, a2, a3;
                    ldsm4t(a0, a1, a2, a3, va + u * TILE_BYTES + k * 2048);
                    zero4(c[k]);
                    mma(c[k], a0, a1, a2, a3, pb[k][0], pb[k][1]);
                }
                const float f0 = (c[0][0] + c[1][0]) + (c[2][0] + c[3][0]), f1 = (c[0][2] + c[1][2]) + (c[2][2] + c[3][2]);
                f = fmaf(a[u], (t & 1) ? f1 : f0, f);
                if (u == 3 && pass && t < 2) ll_store(lp + (vid & 15) * 128 + 8 * t + g, __float_as_uint(f));
                if (pass && tid == 0) sts_volatile(sbase + OFF_DONE, done + u + 1);
                if (u == TUNED(GO) && pass) {
                    if (!late) v = ll_load4(xs);
                    if (isB) { m0 = ll_load2(lm + 2 * g); m1 = ll_load2(lm + 2 * g + 16); }
                }
            }
            if (sw == 0) PROF(10);
        }
        for (unsigned spins = 0; !(ll_ok4(v) && ll_ok4(make_uint4(m0.x, m0.y, m1.x, m1.y))); spins++) {
            __nanosleep(200);
            if (!late) v = ll_load4(xs);
            if (isB) { m0 = ll_load2(lm + 2 * g); m1 = ll_load2(lm + 2 * g + 16); }
            if (spins > SPIN_LIMIT) __trap();
        }
        __syncwarp();
        if (!late) *(uint4*)(smem + OFF_X + (tid >> 6) * (4 * XROW) + (tid & 63) * 16) = make_uint4(~v.x, ~v.y, ~v.z, ~v.w);
        bar_sync(BAR_S, NSW * 32);
        if (sw == 0) PROF(15);
        float w0, w1;
        {
            const float a0 = __uint_as_float(~m0.x), a1 = __uint_as_float(~m1.x), M = redux_max(fmaxf(a0, a1));
            w0 = ex2((a0 - M) * LOG2E), w1 = ex2((a1 - M) * LOG2E);
            float l = w0 * __uint_as_float(~m0.y) + w1 * __uint_as_float(~m1.y);
#pragma unroll
            for (int k = 4; k < 32; k <<= 1) l += __shfl_xor_sync(0xffffffffu, l, k);
            w0 = __fdividef(w0, l), w1 = __fdividef(w1, l);
            if (pass && sw == 0 && !(vid & 15)) *(uint2*)(p.sc->qB + late_pair(vid) * 64 + 2 * lane) = make_uint2(0, 0);
        }
        float acc[4][4];
#pragma unroll
        for (int k = 0; k < 4; k++) zero4(acc[k]);
        uint32_t xf[4][4][4], b[4][4];
        auto rows = [&](int q) {
#pragma unroll
            for (int k = 0; k < 4; k++) ldsm4(xf[q][k][0], xf[q][k][1], xf[q][k][2], xf[q][k][3], xa + q * 256 + k * 64);
        };
        auto load = [&](int q, int h) {
#pragma unroll
            for (int k = 2 * h; k < 2 * h + 2; k++) ldsm4t(b[k][0], b[k][1], b[k][2], b[k][3], wa + q * TILE_BYTES + k * 4096);
        };
        auto mult = [&](int q) {
#pragma unroll
            for (int k = 0; k < 8; k++)
                mma(acc[k & 3], xf[q][k >> 1][0], xf[q][k >> 1][1], xf[q][k >> 1][2], xf[q][k >> 1][3], b[k >> 1][2 * (k & 1)], b[k >> 1][2 * (k & 1) + 1]);
        };
        rows(0); rows(1); rows(2); rows(3);
        mbar_wait(wo, 0);
        load(0, 0); load(0, 1); mult(0);
        if (isB) {
            const int z = lds_volatile(sbase + OFF_WIN + 4) + tiles4(TUNED(TRIG)) * TUNED(TAU) / 512;
            for (int k = pass ? 0 : 63; k < 64 && !__any_sync(0xffffffffu, (int)(now_ns() - z) >= 0); k++) __nanosleep(20);
            if (sw == 0) PROF(27);
            if (pass) { u0 = ll_load4(lp + g * 128 + 4 * t); u1 = ll_load4(lp + g * 128 + 4 * t + 1024); }
        }
        mbar_wait(wo + 8, 0);
        load(1, 0); load(1, 1); mult(1);
        if (isB) {
            for (unsigned spins = 0; !__all_sync(0xffffffffu, ll_ok4(u0) && ll_ok4(u1)); spins++) {
                if (sw == 0 && spins < 3) PROF2(150 + spins);
                u0 = ll_load4(lp + g * 128 + 4 * t); u1 = ll_load4(lp + g * 128 + 4 * t + 1024);
                if (spins > SPIN_LIMIT) __trap();
            }
            if (sw == 0) PROF2(153);
            const float o0 = w0 * __uint_as_float(~u0.x) + w1 * __uint_as_float(~u1.x), o1 = w0 * __uint_as_float(~u0.y) + w1 * __uint_as_float(~u1.y);
            const float o2 = w0 * __uint_as_float(~u0.z) + w1 * __uint_as_float(~u1.z), o3 = w0 * __uint_as_float(~u0.w) + w1 * __uint_as_float(~u1.w);
            const bool hi = lane & 16, mid = lane & 8;
            const float e0 = (hi ? o2 : o0) + __shfl_xor_sync(0xffffffffu, hi ? o0 : o2, 16);
            const float e1 = (hi ? o3 : o1) + __shfl_xor_sync(0xffffffffu, hi ? o1 : o3, 16);
            const float e = (mid ? e1 : e0) + __shfl_xor_sync(0xffffffffu, mid ? e0 : e1, 8);
            *lx = __float2bfloat16_rn(e + __shfl_xor_sync(0xffffffffu, e, 4));
            if (sw == 0) PROF(4);
        }
        bool r2 = mbar_test(wo + 16, 0);
        if (isB) bar_sync(BAR_S, NSW * 32);
        if (isB && g == 3) {
#pragma unroll
            for (int k = 0; k < 4; k++) {
                const uint4 f = lf[4 * k];
                xf[3][k][0] = f.x; xf[3][k][1] = f.y; xf[3][k][2] = f.z; xf[3][k][3] = f.w;
            }
        }
        mbar_wait_unless(r2, wo + 16);
        bool r3 = mbar_test(wo + 24, 0);
        load(2, 0); load(2, 1); mult(2);
        mbar_wait_unless(r3, wo + 24);
        r3 = mbar_try(wo + 32, 0);
        load(3, 0);
        mbar_wait_unless(r3, wo + 32);
        if (sw == 0) PROF(11);
        load(3, 1); mult(3);
        const uint32_t y = pack_bf16((acc[0][0] + acc[1][2]) + (acc[2][0] + acc[3][2]), (acc[0][1] + acc[1][3]) + (acc[2][1] + acc[3][3]));
        asm volatile("{\n .reg .pred q;\n setp.ne.u32 q, %2, 0;\n @q red.relaxed.gpu.global.add.noftz.bf16x2 [%0], %1;\n}"
                     ::"l"(out), "r"(y), "r"((int)(pass && lane < 16)) : "memory");
    }
    if (sw == 7) PROF(25);
    if (sw == 2) PROF(24);
}

__global__ void __launch_bounds__(NTHREADS, 1) fused_decode_kernel(const Ptrs ptrs, const __grid_constant__ Maps maps) {
    extern __shared__ __align__(1024) char smem[];
    Params p;
    static_cast<Ptrs&>(p) = ptrs;
    p.tm = maps.tm;
    const unsigned blk = blockIdx.x;
    asm volatile("{\n .reg .u64 a;\n mad.wide.u32 a, %1, 32, %0;\n prefetch.global.L2 [a];\n}" ::"l"(p.K), "r"(blk * NTHREADS + threadIdx.x) : "memory");
    if (threadIdx.x == 0) first_load(p, smem_u32(smem), blk);
    const int warp = __shfl_sync(0xffffffffu, threadIdx.x >> 5, 0), lane = threadIdx.x & 31;
    const bool isA = blk % APER == APER - 1;
    const int aidx = blk / APER, ab = aidx / SPLIT, asp = aidx % SPLIT;
    const int wk = isA ? NB + aidx : blk - aidx;
    const int vid = !isA ? wk : asp == 3 ? -1 : NB + ab * 3 + asp;
    if (threadIdx.x == 32) next_loads(p, smem_u32(smem), vid);
    if (lane == 0 && warp != 1) {
        const int wu = max(warp, 1);
#pragma unroll
        for (int k = 0; k < (MB_COUNT - MB_EARLY + 10) / 11; k++) {
            const int i = MB_EARLY + k * 11 + wu - 1;
            if (i < MB_COUNT && i != MB_FULL) mbar_init(smem_u32(smem) + OFF_BAR + i * 8, i >= MB_F0 ? NSW : i == MB_PH ? 4 : 1);
        }
        fence_mbar_init();
        if (wu >= 2 && wu < 8) asm volatile("prefetch.tensormap [%0];" ::"l"(&p.tm[wu]) : "memory");
    }
    __syncwarp();
    if (threadIdx.x == 33) {
        *(int2*)(smem + OFF_DONE) = make_int2(0, 0);
        *(int2*)(smem + OFF_WIN) = make_int2(TUNED(WSTART), 0);
    }
    if (warp >= 4 && vid >= 0) clear_handoffs(p, vid, threadIdx.x - 128);
    bar_sync(0, NTHREADS);
    if (warp == 0) {
        produce(p, smem, lane, isA, wk, vid, ab * 4096 + asp * 32);
    } else if (warp < 3) {
        if (isA) softmax_A(p, smem, warp - 1, lane, ab, asp);
        consume(p, smem, isA, wk, vid, warp - 1, lane);
    } else if (warp == 3) {
        service(p, smem, isA, vid, lane);
    } else {
        const int sw = warp - 4;
        if (vid >= 0) side_prologue(p, smem, isA, wk, vid, sw, lane);
        if (isA) attention_A(p, smem, sw, lane, ab, asp, vid < 0);
        if (vid < 0) fill_qtab(p, smem, isA, wk, vid, threadIdx.x - 128);
        if (vid >= 0) side_epilogue(p, smem, vid, sw, lane);
    }
}

__device__ float g_tmp[2][4 * 32 * 512];
__device__ __forceinline__ float bfr(float x) { return __bfloat162float(__float2bfloat16_rn(x)); }
template <typename X>
__global__ void fb_matvec(const X* x, int xb, int xh, int K, const __nv_bfloat16* W, int wk, int wh, int wn, float* y,
                          __nv_bfloat16* out, bool round) {
    const int n = threadIdx.x, h = blockIdx.x, b = blockIdx.y;
    float s = 0.f;
    for (int k = 0; k < K; k++) s += (float)x[b * xb + h * xh + k] * __bfloat162float(W[(size_t)k * wk + h * wh + (size_t)n * wn]);
    if (out) out[b * 1024 + n] = __float2bfloat16_rn(s);
    else y[(b * gridDim.x + h) * blockDim.x + n] = round ? bfr(s) : s;
}
__global__ void fb_attn(const float* q, const __nv_bfloat16* K, const __nv_bfloat16* V, int D, size_t sb, size_t sh, float* o, bool round) {
    __shared__ float sc[4096], red[8];
    const int h = blockIdx.x, b = blockIdx.y, tid = threadIdx.x;
    K += b * sb + h * sh; V += b * sb + h * sh; q += (b * 32 + h) * D;
    float m = -INFINITY, l = 0.f;
    for (int k = tid; k < 4096; k += 256) {
        float s = 0.f;
        for (int d = 0; d < D; d++) s += q[d] * __bfloat162float(K[(size_t)k * D + d]);
        m = fmaxf(m, sc[k] = bfr(bfr(s) * SCALE));
    }
    m = warp_max(m);
    if (!(tid & 31)) red[tid >> 5] = m;
    __syncthreads();
    for (int i = 0; i < 8; i++) m = fmaxf(m, red[i]);
    __syncthreads();
    for (int k = tid; k < 4096; k += 256) { const float e = expf(sc[k] - m); l += e; sc[k] = bfr(e); }
    l = warp_sum(l);
    if (!(tid & 31)) red[tid >> 5] = l;
    __syncthreads();
    l = 0.f;
    for (int i = 0; i < 8; i++) l += red[i];
    for (int d = tid; d < D; d += 256) {
        float s = 0.f;
        for (int k = 0; k < 4096; k++) s += sc[k] * __bfloat162float(V[(size_t)k * D + d]);
        o[(b * 32 + h) * D + d] = round ? bfr(s / l) : s / l;
    }
}
void launch_fallback(void* const* d_in, __nv_bfloat16* out) {
    typedef const __nv_bfloat16* BP;
    float* t0;
    cudaGetSymbolAddress((void**)&t0, g_tmp);
    float* t1 = t0 + 4 * 32 * 512;
    const dim3 gh(32, 4), g1(1, 4);
    fb_matvec<<<gh, 128>>>((BP)d_in[0], 512, 0, 512, (BP)d_in[2], 4096, 128, 1, t0, nullptr, true);
    fb_matvec<<<gh, 512>>>((const float*)t0, 4096, 128, 128, (BP)d_in[3], 1, 128, 4096, t1, nullptr, true);
    fb_attn<<<gh, 256>>>(t1, (BP)d_in[1], (BP)d_in[1], 512, (size_t)4096 * 512, 0, t0, false);
    fb_matvec<<<gh, 128>>>((const float*)t0, 32 * 512, 512, 512, (BP)d_in[4], 4096, 128, 1, t1, nullptr, true);
    fb_matvec<<<g1, 512>>>((const float*)t1, 4096, 0, 4096, (BP)d_in[5], 512, 0, 1, nullptr, out, false);
    fb_matvec<<<gh, 128>>>((BP)d_in[6], 512, 0, 512, (BP)d_in[9], 4096, 128, 1, t0, nullptr, true);
    fb_attn<<<gh, 256>>>(t0, (BP)d_in[7], (BP)d_in[8], 128, (size_t)32 * 4096 * 128, (size_t)4096 * 128, t1, true);
    fb_matvec<<<g1, 512>>>((const float*)t1, 4096, 0, 4096, (BP)d_in[10], 512, 0, 1, nullptr, out + 512, false);
}

typedef CUresult (*EncodeFn)(CUtensorMap*, CUtensorMapDataType, cuuint32_t, void*, const cuuint64_t*, const cuuint64_t*,
                             const cuuint32_t*, const cuuint32_t*, CUtensorMapInterleave, CUtensorMapSwizzle,
                             CUtensorMapL2promotion, CUtensorMapFloatOOBfill);

void make_map(EncodeFn enc, CUtensorMap* tm, void* ptr, uint64_t cols, uint64_t rows, uint32_t br) {
    const cuuint64_t dims[2] = {cols, rows};
    const cuuint64_t strides[1] = {cols * 2};
    const cuuint32_t box[2] = {64, br};
    const cuuint32_t es[2] = {1, 1};
    enc(tm, CU_TENSOR_MAP_DATA_TYPE_BFLOAT16, 2, ptr, dims, strides, box, es, CU_TENSOR_MAP_INTERLEAVE_NONE,
        CU_TENSOR_MAP_SWIZZLE_128B, CU_TENSOR_MAP_L2_PROMOTION_NONE,
        CU_TENSOR_MAP_FLOAT_OOB_FILL_NONE);
}

}

extern "C" void kernel_launch(void* const* d_in, const int* in_sizes, int n_in, void* d_out, int out_size) {
    (void)in_sizes; (void)n_in; (void)out_size;
    void* fn = nullptr;
    cudaDriverEntryPointQueryResult qr;
    cudaGetDriverEntryPoint("cuTensorMapEncodeTiled", &fn, cudaEnableDefault, &qr);
    EncodeFn enc = (EncodeFn)fn;
    int dev = 0, sms = 0, per_sm = 0;
    cudaGetDevice(&dev);
    cudaDeviceGetAttribute(&sms, cudaDevAttrMultiProcessorCount, dev);
    cudaFuncSetAttribute(fused_decode_kernel, cudaFuncAttributeMaxDynamicSharedMemorySize, SMEM_BYTES);
    cudaOccupancyMaxActiveBlocksPerMultiprocessor(&per_sm, fused_decode_kernel, NTHREADS, SMEM_BYTES);
    if (!enc || sms * per_sm < NCTA) {
        launch_fallback(d_in, (__nv_bfloat16*)d_out);
        return;
    }
    Ptrs p;
    Maps m;
    make_map(enc, &m.tm[0], d_in[9], 4096, 512, 128);
    make_map(enc, &m.tm[1], d_in[2], 4096, 512, 128);
    make_map(enc, &m.tm[2], d_in[10], 512, 4096, 64);
    make_map(enc, &m.tm[3], d_in[5], 512, 4096, 64);
    make_map(enc, &m.tm[4], d_in[3], 4096, 512, 128);
    make_map(enc, &m.tm[5], d_in[4], 4096, 512, 128);
    make_map(enc, &m.tm[6], d_in[1], 512, 4 * 4096, 32);
    make_map(enc, &m.tm[7], d_in[8], 128, 128 * 4096, TK);
    p.xA = (const __nv_bfloat16*)d_in[0];
    p.xB = (const __nv_bfloat16*)d_in[6];
    p.K = (const __nv_bfloat16*)d_in[7];
    p.V = (const __nv_bfloat16*)d_in[8];
    p.out = (__nv_bfloat16*)d_out;
    cudaGetSymbolAddress((void**)&p.sc, g_scratch);
    fused_decode_kernel<<<NCTA, NTHREADS, SMEM_BYTES>>>(p, m);
}
```

```cpp
#include <cuda.h>
#include <cuda_runtime.h>
#include <cuda_bf16.h>
#include <stdint.h>

namespace {

#define TV_WSTART 3
#define TV_WMIN0 3
#define TV_WMIN 2
#define TV_IMIN 124
#define TV_LEAD 16
#define TV_LEADE 14
#define TV_WMAXE 3
#define TV_IEND 132
#define TV_TAU 640
#define TV_GAIN 1
#define TV_JUMP 400
#define TV_STAG 80
#define TV_QSLEEP 1600
#define TV_GSLEEP 3000
#define TV_ASLEEP 8
#define TV_ITE 6
#define TV_WESTEP 1
#define TV_CNT0 60
#define TV_MERGE 1
#define TV_MERGE0 6
#define TV_SVC 64
#define TV_GO 2
#define TV_TRIG 573
enum { T_WSTART, T_WMIN0, T_WMIN, T_IMIN, T_LEAD, T_LEADE, T_WMAXE, T_IEND, T_TAU, T_GAIN, T_JUMP, T_STAG, T_QSLEEP, T_GSLEEP, T_ASLEEP, T_ITE, T_WESTEP, T_CNT0, T_MERGE, T_MERGE0, T_SVC, T_GO, T_TRIG, T_COUNT };
#define TUNED(k) (TV_##k)

constexpr int TK = 64;
constexpr int TILE_BYTES = TK * 256;
constexpr int NS = 6;
constexpr int WMAX = 6;
constexpr int NSW = 8;
constexpr int NTHREADS = (4 + NSW) * 32;
constexpr int SPLIT = 4;
constexpr int AKEYS = 4096 / SPLIT;
constexpr int ATILES = AKEYS / 32;
constexpr int ASTAGES = 6;
constexpr int NCTA = 128;
constexpr int APER = 8;
constexpr int NB = NCTA - 4 * SPLIT;
constexpr int R_JOIN = 16, R_LATE = 17, N_EARLY = 120;
static_assert(R_JOIN * NB + (R_LATE - R_JOIN) * NCTA == N_EARLY * 16, "early chunks");
constexpr int I_LAST = 8 * R_LATE + 4;
constexpr int I_BOX = I_LAST + 4;
static_assert(I_LAST % NS + 4 <= NS && (I_LAST - 8 * R_JOIN) % NS + 4 <= NS, "the last V tiles share a lap");
__device__ __forceinline__ int late_pair(int vid) { return N_EARLY + (vid >> 4); }
__device__ __forceinline__ int chunk_of(int r, int vid) { return r * NB + max(r - R_JOIN, 0) * (NCTA - NB) + vid; }
__host__ __device__ constexpr int tiles4(int q) { return NB * q + (q > 32 * R_JOIN ? (NCTA - NB) * (q - 32 * R_JOIN) : 0); }

#define CGRP 16
constexpr int CHUNK_STEP = CGRP * TILE_BYTES;
__device__ __forceinline__ size_t chunk_off(unsigned c) { return (size_t)(4 * c - 3 * (c % CGRP)) * TILE_BYTES; }

constexpr int OFF_RING = 0;
constexpr int OFF_SIDE = NS * TILE_BYTES;
constexpr int OFF_SCR = OFF_SIDE + 98304;
constexpr int OFF_X = OFF_SCR;
constexpr int XROW = 264;
constexpr int OFF_RED = OFF_SCR + 8192;
constexpr int OFF_ARED = OFF_SCR;
constexpr int OFF_AP = OFF_ARED + 4 * 32 * 40 * 4;
constexpr int OFF_AALPHA = OFF_AP + 2 * 32 * 80;
constexpr int OFF_OPART = OFF_AALPHA + 256;
constexpr int OFF_ML = OFF_OPART + 2 * 512;
constexpr int OFF_PH = OFF_ML + 16;
constexpr int OFF_MLO = OFF_PH + 512;
constexpr int OFF_DONE = OFF_MLO + 32;
constexpr int OFF_WIN = OFF_DONE + 8;
constexpr int OFF_VEC = OFF_WIN + 8;
constexpr int OFF_Q = OFF_VEC + 4 * 68 * 4;
constexpr int OFF_BAR = OFF_Q + (R_LATE + 1) * 256;
enum { SI_WQ = 0, SI_WUK = 4, SI_WE = 6, SI_OPART = 10, SI_WO = 12, SI_COUNT = SI_WO + 5 };
enum {
    MB_X = 0, MB_SIDE = 1, MB_EARLY = MB_SIDE + 4,
    MB_FULL = MB_SIDE + SI_COUNT,
    MB_AFULL = MB_FULL + NS,
    MB_CNT = MB_AFULL + ASTAGES,
    MB_PH,
    MB_EMPTY,
    MB_F0 = MB_EMPTY + NS, MB_FU, MB_F2, MB_F3,
    MB_Q,
    MB_COUNT
};
constexpr int SMEM_BYTES = OFF_BAR + MB_COUNT * 8;
static_assert(SMEM_BYTES <= 232448, "smem");
constexpr int BLK_W = OFF_SIDE;
constexpr int BLK_U = OFF_SIDE + 65536;

constexpr int BAR_B = 9  , BAR_S = 2, BAR_R = 5, BAR_P = 6, BAR_E = 7;

constexpr float SCALE = 0.08838834764831845f;
constexpr float LOG2E = 1.4426950408889634f;
constexpr unsigned SPIN_LIMIT = 1u << 22;

struct Scratch {
    float opart[32 * SPLIT * 2048];
    unsigned qB[4 * 2048];
    unsigned qA[4 * 2048];
    unsigned qabs[4 * 8192];
    unsigned ctx[4 * 2048];
    unsigned oB[4 * 2048];
    unsigned part[2048 * 128];
    unsigned pml[2048 * 2];
    float2 ml[32 * SPLIT * 4];
    unsigned prog, pad[31];
    unsigned cnt;
};
__device__ __align__(128) Scratch g_scratch;

struct Ptrs {
    const __nv_bfloat16 *K, *V, *xA, *xB;
    __nv_bfloat16* out;
    Scratch* sc;
};
struct Maps {
    CUtensorMap tm[8];
};
struct Params : Ptrs {
    const CUtensorMap* tm;
};

#define PROF(i)
#define PROF2(i)

__device__ __forceinline__ uint32_t smem_u32(const void* p) { return (uint32_t)__cvta_generic_to_shared(p); }
__device__ __forceinline__ void mbar_init(uint32_t bar, int cnt) {
    asm volatile("mbarrier.init.shared::cta.b64 [%0], %1;" ::"r"(bar), "r"(cnt) : "memory");
}
__device__ __forceinline__ void mbar_expect_tx(uint32_t bar, uint32_t bytes) {
    asm volatile("mbarrier.arrive.expect_tx.shared::cta.b64 _, [%0], %1;" ::"r"(bar), "r"(bytes) : "memory");
}
__device__ __forceinline__ bool mbar_try(uint32_t bar, uint32_t parity) {
    uint32_t ok;
    asm volatile("{\n .reg .pred p;\n mbarrier.try_wait.parity.shared::cta.b64 p, [%1], %2;\n selp.u32 %0, 1, 0, p;\n}"
                 : "=r"(ok) : "r"(bar), "r"(parity) : "memory");
    return ok;
}
__device__ __forceinline__ void mbar_wait(uint32_t bar, uint32_t parity) {
    unsigned spins = 0;
    while (!mbar_try(bar, parity))
        if (++spins > SPIN_LIMIT) __trap();
}
__device__ __forceinline__ void mbar_wait_unless(bool done, uint32_t bar) {
    for (unsigned spins = 0; !done; done = mbar_try(bar, 0))
        if (++spins > SPIN_LIMIT) __trap();
}
__device__ __forceinline__ bool mbar_test(uint32_t bar, uint32_t parity) {
    uint32_t ok;
    asm volatile("{\n .reg .pred p;\n mbarrier.test_wait.parity.shared::cta.b64 p, [%1], %2;\n selp.u32 %0, 1, 0, p;\n}"
                 : "=r"(ok) : "r"(bar), "r"(parity) : "memory");
    return ok;
}
__device__ __forceinline__ void warp_release(uint32_t bar, int lane, float dep) {
    const uint32_t any = __ballot_sync(0xffffffffu, dep != dep);
    if (lane == 0)
        asm volatile("{\n .reg .pred q;\n setp.eq.u32 q, %1, 0;\n @q mbarrier.arrive.shared::cta.b64 _, [%0];\n"
                     " @!q mbarrier.arrive.shared::cta.b64 _, [%0];\n}" ::"r"(bar), "r"(any) : "memory");
}
__device__ __forceinline__ bool elect_one() {
    uint32_t e;
    asm volatile("{\n .reg .pred p;\n elect.sync _|p, 0xffffffff;\n selp.u32 %0, 1, 0, p;\n}" : "=r"(e));
    return e;
}
__device__ __forceinline__ int lds_volatile(uint32_t addr) {
    int v;
    asm volatile("ld.volatile.shared.u32 %0, [%1];" : "=r"(v) : "r"(addr) : "memory");
    return v;
}
__device__ __forceinline__ int2 lds_volatile2(uint32_t addr) {
    int2 v;
    asm volatile("ld.volatile.shared.v2.u32 {%0, %1}, [%2];" : "=r"(v.x), "=r"(v.y) : "r"(addr) : "memory");
    return v;
}
__device__ __forceinline__ void sts_volatile2(uint32_t addr, int a, int b) {
    asm volatile("st.volatile.shared.v2.u32 [%0], {%1, %2};" ::"r"(addr), "r"(a), "r"(b) : "memory");
}
__device__ __forceinline__ void sts_volatile(uint32_t addr, int v) {
    asm volatile("st.volatile.shared.u32 [%0], %1;" ::"r"(addr), "r"(v) : "memory");
}
__device__ __forceinline__ unsigned now_ns() {
    unsigned t;
    asm volatile("mov.u32 %0, %%globaltimer_lo;" : "=r"(t) :: "memory");
    return t;
}
__device__ __forceinline__ int clock_after(unsigned dep) {
    int c;
    asm volatile("{\n .reg .pred q;\n setp.eq.u32 q, %1, 0;\n @q mov.u32 %0, %%globaltimer_lo;\n @!q mov.u32 %0, %%globaltimer_lo;\n}" : "=r"(c) : "r"(dep) : "memory");
    return c;
}
__device__ __forceinline__ void fence_mbar_init() { asm volatile("fence.mbarrier_init.release.cluster;" ::: "memory"); }
__device__ __forceinline__ uint64_t policy_evict_first() {
    uint64_t pol;
    asm volatile("createpolicy.fractional.L2::evict_first.b64 %0, 1.0;" : "=l"(pol));
    return pol;
}
__device__ __forceinline__ uint64_t policy_evict_normal() {
    uint64_t pol;
    asm volatile("createpolicy.fractional.L2::evict_normal.b64 %0, 1.0;" : "=l"(pol));
    return pol;
}
__device__ __forceinline__ void bulk_load(uint32_t dst, const void* src, uint32_t bytes, uint32_t bar, uint64_t pol) {
    asm volatile("cp.async.bulk.shared::cluster.global.mbarrier::complete_tx::bytes.L2::cache_hint [%0], [%1], %2, [%3], %4;"
                 ::"r"(dst), "l"(src), "r"(bytes), "r"(bar), "l"(pol) : "memory");
}
__device__ __forceinline__ void bulk_load_nohint(uint32_t dst, const void* src, uint32_t bytes, uint32_t bar) {
    asm volatile("cp.async.bulk.shared::cluster.global.mbarrier::complete_tx::bytes [%0], [%1], %2, [%3];"
                 ::"r"(dst), "l"(src), "r"(bytes), "r"(bar) : "memory");
}
__device__ __forceinline__ void tma2d_hint(uint32_t dst, const CUtensorMap* tm, int x, int y, uint32_t bar, uint64_t pol) {
    asm volatile("cp.async.bulk.tensor.2d.shared::cluster.global.mbarrier::complete_tx::bytes.L2::cache_hint [%0], [%1, {%3, %4}], [%2], %5;"
                 ::"r"(dst), "l"(tm), "r"(bar), "r"(x), "r"(y), "l"(pol) : "memory");
}
__device__ __forceinline__ void ldsm4(uint32_t& r0, uint32_t& r1, uint32_t& r2, uint32_t& r3, uint32_t addr) {
    asm volatile("ldmatrix.sync.aligned.m8n8.x4.shared.b16 {%0,%1,%2,%3}, [%4];"
                 : "=r"(r0), "=r"(r1), "=r"(r2), "=r"(r3) : "r"(addr) : "memory");
}
__device__ __forceinline__ void ldsm4t(uint32_t& r0, uint32_t& r1, uint32_t& r2, uint32_t& r3, uint32_t addr) {
    asm volatile("ldmatrix.sync.aligned.m8n8.x4.trans.shared.b16 {%0,%1,%2,%3}, [%4];"
                 : "=r"(r0), "=r"(r1), "=r"(r2), "=r"(r3) : "r"(addr) : "memory");
}
__device__ __forceinline__ void mma(float (&c)[4], uint32_t a0, uint32_t a1, uint32_t a2, uint32_t a3, uint32_t b0, uint32_t b1) {
    asm volatile("mma.sync.aligned.m16n8k16.row.col.f32.bf16.bf16.f32 {%0,%1,%2,%3}, {%4,%5,%6,%7}, {%8,%9}, {%0,%1,%2,%3};"
                 : "+f"(c[0]), "+f"(c[1]), "+f"(c[2]), "+f"(c[3])
                 : "r"(a0), "r"(a1), "r"(a2), "r"(a3), "r"(b0), "r"(b1));
}
__device__ __forceinline__ void zero4(float (&c)[4]) { c[0] = c[1] = c[2] = c[3] = 0.f; }
__device__ __forceinline__ void bar_sync(int id, int n) { asm volatile("bar.sync %0, %1;" ::"r"(id), "r"(n) : "memory"); }
__device__ __forceinline__ void bar_arrive(int id, int n) { asm volatile("bar.arrive %0, %1;" ::"r"(id), "r"(n) : "memory"); }
__device__ __forceinline__ float ex2(float x) { float y; asm("ex2.approx.ftz.f32 %0, %1;" : "=f"(y) : "f"(x)); return y; }
__device__ __forceinline__ uint32_t pack_bf16(float lo, float hi) {
    uint32_t r; asm("cvt.rn.bf16x2.f32 %0, %1, %2;" : "=r"(r) : "f"(hi), "f"(lo)); return r;
}
__device__ __forceinline__ float bf_lo(uint32_t u) { return __uint_as_float(u << 16); }
__device__ __forceinline__ float bf_hi(uint32_t u) { return __uint_as_float(u & 0xffff0000u); }
__device__ __forceinline__ uint32_t score_round2(float a, float b) {
    const uint32_t u = pack_bf16(a, b);
    return pack_bf16(bf_lo(u) * SCALE, bf_hi(u) * SCALE);
}
__device__ __forceinline__ float warp_max(float v) {
#pragma unroll
    for (int o = 16; o > 0; o >>= 1) v = fmaxf(v, __shfl_xor_sync(0xffffffffu, v, o));
    return v;
}
__device__ __forceinline__ float redux_max(float v) {
    const int i = __float_as_int(v), m = __reduce_max_sync(0xffffffffu, i ^ ((i >> 31) & 0x7fffffff));
    return __int_as_float(m ^ ((m >> 31) & 0x7fffffff));
}
__device__ __forceinline__ float warp_sum(float v) {
#pragma unroll
    for (int o = 16; o > 0; o >>= 1) v += __shfl_xor_sync(0xffffffffu, v, o);
    return v;
}

__device__ __forceinline__ void ll_store(unsigned* p, unsigned bits) {
    unsigned u = ~bits;
    u = u ? u : 0x80008000u;
    asm volatile("st.relaxed.gpu.global.u32 [%0], %1;" ::"l"(p), "r"(u) : "memory");
}
__device__ __forceinline__ void ll_store2(unsigned* p, unsigned a, unsigned b) {
    unsigned u = ~a, v = ~b;
    u = u ? u : 0x80008000u;
    v = v ? v : 0x80008000u;
    asm volatile("st.relaxed.gpu.global.v2.u32 [%0], {%1, %2};" ::"l"(p), "r"(u), "r"(v) : "memory");
}
__device__ __forceinline__ void ll_store4(unsigned* p, float a, float b, float c, float d) {
    unsigned u[4] = {~__float_as_uint(a), ~__float_as_uint(b), ~__float_as_uint(c), ~__float_as_uint(d)};
#pragma unroll
    for (int k = 0; k < 4; k++) u[k] = u[k] ? u[k] : 0x80008000u;
    asm volatile("st.relaxed.gpu.global.v4.u32 [%0], {%1, %2, %3, %4};" ::"l"(p), "r"(u[0]), "r"(u[1]), "r"(u[2]), "r"(u[3]) : "memory");
}
__device__ __forceinline__ unsigned ll_load(const unsigned* p) {
    unsigned u;
    asm volatile("ld.relaxed.gpu.global.u32 %0, [%1];" : "=r"(u) : "l"(p) : "memory");
    return u;
}
__device__ __forceinline__ uint2 ll_load2(const unsigned* p) {
    uint2 v;
    asm volatile("ld.relaxed.gpu.global.v2.u32 {%0,%1}, [%2];" : "=r"(v.x), "=r"(v.y) : "l"(p) : "memory");
    return v;
}
__device__ __forceinline__ uint4 ll_load4(const unsigned* p) {
    uint4 v;
    asm volatile("ld.relaxed.gpu.global.v4.u32 {%0,%1,%2,%3}, [%4];" : "=r"(v.x), "=r"(v.y), "=r"(v.z), "=r"(v.w) : "l"(p) : "memory");
    return v;
}
__device__ __forceinline__ bool ll_ok4(const uint4& v) { return min(min(v.x, v.y), min(v.z, v.w)) != 0u; }
template <int N>
__device__ __forceinline__ void ll_poll4(uint4 (&v)[N], const unsigned* p, int stride, unsigned sleep_ns = 0) {
    unsigned spins = 0;
    while (true) {
        bool ok = true;
#pragma unroll
        for (int k = 0; k < N; k++) v[k] = ll_load4(p + k * stride);
#pragma unroll
        for (int k = 0; k < N; k++) ok = ok && ll_ok4(v[k]);
        if (ok) break;
        if (sleep_ns) __nanosleep(sleep_ns);
        if (++spins > SPIN_LIMIT) __trap();
    }
    __syncwarp();
#pragma unroll
    for (int k = 0; k < N; k++) v[k] = make_uint4(~v[k].x, ~v[k].y, ~v[k].z, ~v[k].w);
}

__device__ __forceinline__ void bump_counter(unsigned* c) {
    asm volatile("red.relaxed.gpu.global.inc.u32 [%0], %1;" ::"l"(c), "r"(4 * SPLIT + 128 - 1) : "memory");
}
__device__ __forceinline__ void signal_counter(unsigned* c) {
    asm volatile("fence.acq_rel.gpu;" ::: "memory");
    bump_counter(c);
}
__device__ __forceinline__ unsigned ld_acquire(const unsigned* c) {
    unsigned v;
    asm volatile("ld.acquire.gpu.global.u32 %0, [%1];" : "=r"(v) : "l"(c) : "memory");
    return v;
}
__device__ __forceinline__ uint32_t pv_mask(int c, int g, int t) {
    return (c == (g ^ (2 * t)) ? 0x0000ffffu : 0u) | (c == (g ^ (2 * t + 1)) ? 0xffff0000u : 0u);
}

struct Producer {
    uint32_t sbase;
    uint32_t wbar, wpar;
    bool pend;
    int lane;
    uint64_t pol;
    uint32_t si_dst, si_gate;
    int si_x, si_y, si_min;
    bool si_box;
    const void* si_src;
    uint64_t si_pol;
    __device__ __forceinline__ uint32_t mb(int i) const { return sbase + OFF_BAR + i * 8; }
    __device__ __forceinline__ void setup_side(const Params& p, int vid) {
        const int cbk = vid >> 1, u = lane & 1;
        si_box = true; si_min = 0; si_gate = mb(MB_X);
        si_pol = lane >= SI_OPART ? policy_evict_normal() : pol;
        int blk = BLK_U + u * 16384;
        if (lane >= SI_OPART) {
            si_box = false; si_src = p.sc->opart + ((cbk >> 1) * SPLIT + 2 * u) * 2048;
            si_gate = mb(MB_CNT);
        } else if (lane >= SI_WE) {
            const int q = lane - SI_WE;
            si_src = &p.tm[5]; blk = BLK_W + q * 16384;
            si_x = 64 * cbk; si_y = 128 * q;
            si_gate = mb(MB_F0); si_min = TUNED(ITE) + TUNED(WESTEP) * q;
        } else {
            si_src = &p.tm[4]; si_x = (vid & 31) * 128 + 64 * u; si_y = 128 * (vid >> 5);
        }
        si_dst = sbase + blk;
    }
    __device__ __forceinline__ bool due(const Params& p, int i, int2 st) const {
        return st.y && (int)(now_ns() - st.y) >= tiles4(4 * i - (i < TUNED(IEND) ? TUNED(LEAD) : TUNED(LEADE))) * TUNED(TAU) / 512;
    }
    __device__ __forceinline__ void window(const Params& p, int i, uint32_t bar, uint32_t parity) {
        unsigned busy;
        for (unsigned spins = 0;; spins++) {
            const int2 st = lds_volatile2(sbase + OFF_WIN);
            if (pend) pend = !mbar_test(wbar, wpar);
            busy = __ballot_sync(0xffffffffu, pend);
            const int n = __popc(busy);
            if (__any_sync(0xffffffffu, n < st.x || (n < (i < TUNED(IEND) ? WMAX : TUNED(WMAXE)) && due(p, i, st)))) break;
            if (spins > 16 * SPIN_LIMIT) __trap();
        }
        if (lane == __ffs(~busy) - 1) { wbar = bar; wpar = parity; pend = true; }
    }
    __device__ __forceinline__ void side(const Params& p, int id) {
        const uint32_t bar = mb(MB_SIDE + id);
        if (id < SI_OPART) window(p, 0, bar, 0);
        if (lane == id) {
            mbar_expect_tx(bar, TILE_BYTES);
            if (si_box) {
                tma2d_hint(si_dst, (const CUtensorMap*)si_src, si_x, si_y, bar, si_pol);
            } else {
                asm volatile("fence.proxy.async.global;" ::: "memory");
                bulk_load(si_dst, si_src, TILE_BYTES, bar, si_pol);
            }
        }
        __syncwarp();
    }
    __device__ __forceinline__ void a_tile(const Params& p, int row0, int n) {
        const int st = n % ASTAGES;
        if (lane == 0) mbar_expect_tx(mb(MB_AFULL + st), 32768);
        __syncwarp();
        if (lane < 8) tma2d_hint(sbase + st * 32768 + lane * 4096, &p.tm[6], lane * 64, row0 + n * (32 * SPLIT), mb(MB_AFULL + st), pol);
        __syncwarp();
    }
};

__device__ __forceinline__ void first_load(const Params& p, uint32_t sbase, unsigned blk) {
    const uint32_t bar = sbase + OFF_BAR + MB_FULL * 8;
    mbar_init(bar, 1);
    if (blk % APER != APER - 1) {
        const unsigned c = blk - blk / APER;
        fence_mbar_init();
        mbar_expect_tx(bar, TILE_BYTES);
        bulk_load(sbase + OFF_RING, (const char*)p.K + chunk_off(c), TILE_BYTES, bar, policy_evict_first());
    }
}
__device__ __forceinline__ void next_loads(const Params& p, uint32_t sbase, int vid) {
    const uint32_t bars = sbase + OFF_BAR;
    const uint64_t pol = policy_evict_first();
#pragma unroll
    for (int i = 0; i < MB_EARLY; i++) mbar_init(bars + i * 8, 1);
    fence_mbar_init();
#pragma unroll
    for (int q = 0; q < 4; q++) {
        mbar_expect_tx(bars + (MB_SIDE + q) * 8, TILE_BYTES);
        tma2d_hint(sbase + BLK_W + q * 16384, &p.tm[vid & 1], 64 * (vid >> 1), 128 * q, bars + (MB_SIDE + q) * 8, pol);
        if (q == 0) {
            mbar_expect_tx(bars + MB_X * 8, 4096);
            bulk_load_nohint(sbase + OFF_X, (vid & 1) ? p.xA : p.xB, 4096, bars + MB_X * 8);
        }
    }
}

__device__ __forceinline__ void produce(const Params& p, char* smem, int lane, bool isA, int vid, int row0) {
    Producer pr;
    pr.sbase = smem_u32(smem);
    pr.lane = lane;
    pr.pol = policy_evict_first();
    pr.pend = !isA && lane < 5;
    pr.wbar = pr.mb(lane == 0 ? MB_FULL : MB_SIDE + lane - 1);
    pr.wpar = 0;
    pr.setup_side(p, vid);
    const int i0 = isA ? 8 * R_JOIN : 0;
    int i = isA ? i0 : 1, i_end = isA ? i0 : I_LAST, s = i - i0, ph = 0;
    int chunk = chunk_of(i >> 3, vid);
    const char* src = (const char*)p.K + chunk_off(chunk) + (i & 3) * CHUNK_STEP;
    int nx = SI_WUK, nx_end = isA || (vid & 1) ? SI_WE : SI_WO;
    uint32_t gate = pr.mb(MB_X);
    int gmin = 0;
    bool last_tile = false;
#pragma unroll 1
    for (int phase = 0; phase < 3; phase++) {
#pragma unroll 1
        while (i < i_end || nx < nx_end) {
            if (nx < nx_end && i >= gmin) {
                bool side = true;
                if (i == i_end) mbar_wait(gate, 0);
                else side = __all_sync(0xffffffffu, mbar_test(gate, 0) &&
                                       (last_tile || (i - i0 >= NS && !mbar_test(pr.mb(MB_EMPTY + s), ph ^ 1))));
                if (side) {
                    last_tile = false;
                    pr.side(p, nx);
                    PROF2(160 + nx);
                    nx++;
                    gate = __shfl_sync(0xffffffffu, pr.si_gate, nx);
                    gmin = __shfl_sync(0xffffffffu, pr.si_min, nx);
                    continue;
                }
            }
            last_tile = true;
            const uint32_t full = pr.mb(MB_FULL + s);
            mbar_wait(pr.mb(MB_EMPTY + s), ph ^ 1);
            if (elect_one()) mbar_expect_tx(full, TILE_BYTES);
            pr.window(p, i, full, ph);
            if (elect_one()) bulk_load(pr.sbase + OFF_RING + s * TILE_BYTES, src, TILE_BYTES, full, pr.pol);
            PROF2(i);
            src += CHUNK_STEP;
            if ((++i & 3) == 0) {
                if ((i & 4) == 0) chunk = chunk_of(i >> 3, vid);
                src = (const char*)((i & 4) ? p.V : p.K) + chunk_off(chunk);
            }
            if (++s == NS) { s = 0; ph ^= 1; }
        }
        if (!isA || phase == 2) break;
        if (phase == 0) {
#pragma unroll 1
            for (int k = -ASTAGES; k < ATILES; k++) {
                if (k == 3 - ASTAGES) mbar_wait(pr.mb(MB_FU), 0);
                if (k >= 0) bar_sync(BAR_R, 352);
                const int n = k < 0 ? k + ASTAGES : k - 2 + ASTAGES;
                if ((k < 0 || k >= 2) && n < ATILES) { pr.a_tile(p, row0, n); PROF2(32 + n); }
            }
            mbar_wait(pr.mb(MB_F3), 0);
            if (!(vid & 1)) nx_end = SI_WO;
        } else {
            for (int k = 0; k < 500 && !__any_sync(0xffffffffu, pr.due(p, i0, lds_volatile2(pr.sbase + OFF_WIN))); k++) __nanosleep(100);
            i_end = I_LAST;
        }
    }
#pragma unroll 1
    for (int u = 0; u < 4; u++) {
        const uint32_t full = pr.mb(MB_FULL + s + u);
        mbar_wait(pr.mb(MB_EMPTY + s + u), ph ^ 1);
        if (elect_one()) mbar_expect_tx(full, TILE_BYTES);
        pr.window(p, I_LAST + u, full, ph);
        if (elect_one()) {
#pragma unroll
            for (int hf = 0; hf < 2; hf++)
                tma2d_hint(pr.sbase + OFF_RING + (s + u) * TILE_BYTES + hf * 8192, &p.tm[7], 64 * hf,
                           (chunk_off(chunk) + u * CHUNK_STEP) / 256, full, pr.pol);
        }
        PROF2(I_LAST + u);
    }
    mbar_wait(pr.mb((vid & 1) ? MB_F0 : MB_F2), 0);
#pragma unroll 1
    for (int u = 0; u < 4; u++) {
        const uint32_t bar = pr.mb(MB_SIDE + SI_WO + u);
        if (elect_one()) {
            mbar_expect_tx(bar, u < 3 ? TILE_BYTES : TILE_BYTES / 2);
            if (u == 3) mbar_expect_tx(bar + 8, TILE_BYTES / 2);
        }
        pr.window(p, I_BOX + u, bar, 0);
        if (elect_one()) {
#pragma unroll
            for (int k = 0; k < 2; k++)
                tma2d_hint(pr.sbase + BLK_W + u * TILE_BYTES + k * (TILE_BYTES / 2), &p.tm[2 + (vid & 1)], 64 * ((vid >> 1) & 7),
                           1024 * u + 128 * (vid >> 4) + 64 * k, bar + (u == 3 ? 8 * k : 0), pr.pol);
        }
        PROF2(I_BOX + u);
    }
}

__device__ __forceinline__ void consume(const Params& p, char* smem, bool isA, int vid, int w, int lane) {
    const uint32_t sbase = smem_u32(smem);
    const uint32_t bars = sbase + OFF_BAR;
    const int g = lane >> 2, t = lane & 3;
    const int mat = lane >> 3, r8 = lane & 7;
    const uint32_t kbase = sbase + OFF_RING + (r8 + 8 * (mat & 1)) * 256 + (mat >> 1) * 128 + r8 * 16;
    const uint32_t vbase = sbase + OFF_RING + (r8 + 8 * (mat >> 1)) * 256 + (mat & 1) * 128 + r8 * 16;
    uint32_t mask[8];
#pragma unroll
    for (int c = 0; c < 8; c++) mask[c] = pv_mask(c, g, t);
    uint32_t* qtab = (uint32_t*)(smem + OFF_Q);
    if (!isA) {
        mbar_wait(bars + MB_F0 * 8, 0);
        __nanosleep(TUNED(QSLEEP));
        const unsigned* src = p.sc->qB + (chunk_of(0, vid) >> 4) * 64 + lane;
        unsigned q0, q1, spins = 0;
        while (true) {
            q0 = ll_load(src);
            q1 = ll_load(src + 32);
            if (q0 && q1) break;
            __nanosleep(200);
            if (++spins > SPIN_LIMIT) __trap();
        }
        qtab[lane] = ~q0;
        qtab[32 + lane] = ~q1;
        __syncwarp();
        if (w == 0) PROF(1);
    }
    int s = w, ph = 0;
    int done = 0;
#pragma unroll 1
    for (int r = isA ? R_JOIN : 0;; r++) {
        const int chunk = chunk_of(r, vid);
        if (r >= 1) mbar_wait(bars + MB_Q * 8, 0);
        uint32_t qf[8][2];
#pragma unroll
        for (int c = 0; c < 8; c++) {
            qf[c][0] = qtab[r * 64 + (c ^ g) * 4 + t];
            qf[c][1] = qtab[r * 64 + 32 + (c ^ g) * 4 + t];
        }
        uint32_t pf[2][4][2];
        float m[2], l[2];
#pragma unroll
        for (int u = 0; u < 2; u++) {
            mbar_wait(bars + (MB_FULL + s) * 8, ph);
            done++;
            float acc[4][4];
#pragma unroll
            for (int gr = 0; gr < 4; gr++) zero4(acc[gr]);
#pragma unroll
            for (int c = 0; c < 8; c++) {
#pragma unroll
                for (int gr = 0; gr < 4; gr++) {
                    uint32_t a0, a1, a2, a3;
                    ldsm4(a0, a1, a2, a3, (kbase ^ (c << 4)) + s * TILE_BYTES + gr * 4096);
                    mma(acc[gr], a0, a1, a2, a3, qf[c][0], qf[c][1]);
                }
            }
            warp_release(bars + (MB_EMPTY + s) * 8, lane, (acc[0][0] + acc[1][0]) + (acc[2][0] + acc[3][0]));
#pragma unroll
            for (int gr = 0; gr < 4; gr++) {
                const uint32_t su = score_round2((g & 1) ? acc[gr][1] : acc[gr][0], (g & 1) ? acc[gr][3] : acc[gr][2]);
                const uint32_t x = __shfl_sync(0xffffffffu, su, 9 * t), y = __shfl_sync(0xffffffffu, su, 9 * t + 4);
                pf[u][gr][0] = __byte_perm(x, y, 0x5410);
                pf[u][gr][1] = __byte_perm(x, y, 0x7632);
            }
            m[u] = -INFINITY;
            l[u] = 0.f;
#pragma unroll
            for (int k = 0; k < 8; k++) m[u] = fmaxf(m[u], fmaxf(bf_lo(pf[u][k >> 1][k & 1]), bf_hi(pf[u][k >> 1][k & 1])));
            m[u] = fmaxf(m[u], __shfl_xor_sync(0xffffffffu, m[u], 1));
            m[u] = fmaxf(m[u], __shfl_xor_sync(0xffffffffu, m[u], 2));
#pragma unroll
            for (int k = 0; k < 8; k++) {
                uint32_t& x = pf[u][k >> 1][k & 1];
                const float e0 = ex2((bf_lo(x) - m[u]) * LOG2E), e1 = ex2((bf_hi(x) - m[u]) * LOG2E);
                l[u] += e0 + e1;
                x = pack_bf16(e0, e1);
            }
            l[u] += __shfl_xor_sync(0xffffffffu, l[u], 1);
            l[u] += __shfl_xor_sync(0xffffffffu, l[u], 2);
            if (lane == 0) sts_volatile(sbase + OFF_DONE + 4 * w, done);
            if (r == R_LATE) {
                if (lane < 4) {
                    uint4* dst = (uint4*)(smem + OFF_PH + (2 * u + w) * 128 + t * 32);
                    dst[0] = make_uint4(pf[u][0][0], pf[u][0][1], pf[u][1][0], pf[u][1][1]);
                    dst[1] = make_uint4(pf[u][2][0], pf[u][2][1], pf[u][3][0], pf[u][3][1]);
                    if (lane == 0) ((float2*)(smem + OFF_MLO))[2 * u + w] = make_float2(m[u], l[u]);
                }
                __syncwarp();
                if (lane == 0) mbar_expect_tx(bars + MB_PH * 8, 0);
            }
            if ((s += 2) >= NS) { s -= NS; ph ^= 1; }
        }
        if (r == R_LATE) break;
        const float mw = fmaxf(m[0], m[1]);
        float o[4] = {0.f, 0.f, 0.f, 0.f}, lw = 0.f;
#pragma unroll
        for (int u = 0; u < 2; u++) {
            const float a = ex2((m[u] - mw) * LOG2E);
            lw = fmaf(a, l[u], lw);
            float oacc[4][4];
#pragma unroll
            for (int gr = 0; gr < 4; gr++) zero4(oacc[gr]);
            mbar_wait(bars + (MB_FULL + s) * 8, ph);
            PROF(u ? 2 + w : 19 + w);
            done++;
#pragma unroll
            for (int c = 0; c < 8; c++) {
#pragma unroll
                for (int gr = 0; gr < 4; gr++) {
                    uint32_t a0, a1, a2, a3;
                    ldsm4t(a0, a1, a2, a3, (vbase ^ (c << 4)) + s * TILE_BYTES + gr * 4096);
                    mma(oacc[gr], a0, a1, a2, a3, pf[u][gr][0] & mask[c], pf[u][gr][1] & mask[c]);
                }
            }
#pragma unroll
            for (int e = 0; e < 4; e++) o[e] = fmaf(a, (oacc[0][e] + oacc[1][e]) + (oacc[2][e] + oacc[3][e]), o[e]);
            warp_release(bars + (MB_EMPTY + s) * 8, lane, o[0]);
            if (lane == 0) sts_volatile(sbase + OFF_DONE + 4 * w, done);
            if ((s += 2) >= NS) { s -= NS; ph ^= 1; }
        }
        float4* op = (float4*)(smem + OFF_OPART) + (r & 1) * 32 + lane;
        float2* ml = (float2*)(smem + OFF_ML) + (r & 1);
        if (w == 0) {
            *op = make_float4(o[0], o[1], o[2], o[3]);
            if (lane == 0) *ml = make_float2(mw, lw);
            bar_arrive(BAR_B + (r & 1), 64);
        } else {
            bar_sync(BAR_B + (r & 1), 64);
            const float2 ot = *ml;
            const float4 oo = *op;
            const float M = fmaxf(mw, ot.x), a = ex2((mw - M) * LOG2E), b = ex2((ot.x - M) * LOG2E);
            ll_store4(p.sc->part + chunk * 128 + lane * 4, a * o[0] + b * oo.x, a * o[1] + b * oo.y,
                      a * o[2] + b * oo.z, a * o[3] + b * oo.w);
            if (lane == 0) ll_store2(p.sc->pml + chunk * 2, __float_as_uint(M), __float_as_uint(a * lw + b * ot.y));
            PROF(10);
        }
    }
}

__device__ __forceinline__ uint2 merge_chunks(const Params& p, int pair, int lane) {
    Scratch* sc = p.sc;
    const unsigned* pm = sc->pml + pair * 32 + 2 * (lane & 15);
    const unsigned* base = sc->part + pair * 2048 + 4 * lane;
    unsigned um = 0, ul = 0;
    uint4 u[16];
#pragma unroll
    for (int c = 0; c < 16; c++) u[c] = make_uint4(0, 0, 0, 0);
    for (unsigned spins = 0;; spins++) {
        if (!(um && ul)) { um = ll_load(pm); ul = ll_load(pm + 1); }
#pragma unroll
        for (int c = 0; c < 16; c++)
            if (!ll_ok4(u[c])) u[c] = ll_load4(base + c * 128);
        bool ok = um && ul;
#pragma unroll
        for (int c = 0; c < 16; c++) ok &= ll_ok4(u[c]);
        if (__all_sync(0xffffffffu, ok)) break;
        __nanosleep(100);
        if (spins > SPIN_LIMIT) __trap();
    }
    const float m = __uint_as_float(~um);
    const float M = redux_max(m);
    const float wgt = ex2((m - M) * LOG2E);
    float l = wgt * __uint_as_float(~ul);
#pragma unroll
    for (int k = 8; k > 0; k >>= 1) l += __shfl_xor_sync(0xffffffffu, l, k);
    float o[4] = {0.f, 0.f, 0.f, 0.f};
#pragma unroll
    for (int c = 0; c < 16; c++) {
        const float wc = __shfl_sync(0xffffffffu, wgt, c);
        o[0] = fmaf(wc, __uint_as_float(~u[c].x), o[0]); o[1] = fmaf(wc, __uint_as_float(~u[c].y), o[1]);
        o[2] = fmaf(wc, __uint_as_float(~u[c].z), o[2]); o[3] = fmaf(wc, __uint_as_float(~u[c].w), o[3]);
    }
    const float inv = __frcp_rn(l);
    const uint32_t lo = pack_bf16(o[0] * inv, o[2] * inv), hi = pack_bf16(o[1] * inv, o[3] * inv);
    const bool odd = lane & 4;
    const uint32_t x = __shfl_xor_sync(0xffffffffu, odd ? lo : hi, 4), a = odd ? x : lo, b = odd ? hi : x;
    return make_uint2(__byte_perm(a, b, 0x5410), __byte_perm(a, b, 0x7632));
}

__device__ __forceinline__ int qabs_word(int b, int h, int j, int ks, int nt, int t) {
    return b * 8192 + (((h >> 4) + 2 * j) * 8 + ks) * 128 + ((h & 7) * 4 + t) * 4 + ((h >> 3) & 1) + 2 * nt;
}
__device__ __forceinline__ void service(const Params& p, char* smem, bool isA, int vid, int lane) {
    const uint32_t sbase = smem_u32(smem);
    const int i0 = isA ? 8 * R_JOIN : 0;
    const int c = 16 * vid + 15;
    const int rl = c < R_JOIN * NB ? c / NB : R_JOIN + (c - R_JOIN * NB) / NCTA;
    const int due = 8 * (rl + 1) + (rl + 1 == R_LATE ? TUNED(MERGE) : TUNED(MERGE0));
    const int ow = 8 * (lane & 3) + (lane & 4) + (lane >> 3);
    bool merged = vid >= N_EARLY, counted = false;
    int last = i0, z = 0;
    unsigned t0 = clock(), t1 = t0, prev = 0;
    if (isA) mbar_wait(sbase + OFF_BAR + MB_F3 * 8, 0);
    for (unsigned spins = 0; last < I_BOX || !counted || !merged; spins++) {
        const int pos = __shfl_sync(0xffffffffu, i0 + lds_volatile(sbase + OFF_DONE) + lds_volatile(sbase + OFF_DONE + 4), 0);
        if (!merged && pos > due) {
            const int pair = vid;
            const uint2 o = merge_chunks(p, pair, lane);
            ll_store(p.sc->oB + pair * 64 + ow, o.x);
            ll_store(p.sc->oB + pair * 64 + ow + 32, o.y);
#pragma unroll
            for (int k = 0; k < 16; k++) *(uint4*)(p.sc->part + pair * 2048 + k * 128 + 4 * lane) = make_uint4(0, 0, 0, 0);
            p.sc->pml[pair * 32 + lane] = 0;
            *(uint2*)(p.sc->qB + pair * 64 + 2 * lane) = make_uint2(0, 0);
            PROF(12);
            merged = true;
            continue;
        }
        const unsigned now = __shfl_sync(0xffffffffu, (unsigned)clock(), 0);
        const bool look = pos > last || (isA && pos == i0 && now - t1 > 2000);
        unsigned old = 0;
        if (look && lane == 0) old = pos > last ? atomicAdd(&p.sc->prog, pos - last) : ll_load(&p.sc->prog);
        if (!counted && now - t0 > 2000 && (isA || pos > TUNED(CNT0))) {
            t0 = now;
            if (__all_sync(0xffffffffu, ld_acquire(&p.sc->cnt) >= 4 * SPLIT)) {
                if (lane == 0) {
                    mbar_expect_tx(sbase + OFF_BAR + MB_CNT * 8, 0);
                    bump_counter(&p.sc->cnt);
                }
                *(uint2*)(p.sc->qA + vid * 64 + lane * 2) = make_uint2(0, 0);
                *(uint4*)(p.sc->qabs + vid * 256 + lane * 4) = make_uint4(0, 0, 0, 0);
                *(uint4*)(p.sc->qabs + vid * 256 + 128 + lane * 4) = make_uint4(0, 0, 0, 0);
                counted = true;
            }
        }
        if (look) {
            if (lane == 0) {
                if (pos > last && old + (pos - last) == tiles4(4 * I_BOX) / 4) p.sc->prog = 0;
                if (old > prev && old >= 6 * NB && old < tiles4(4 * I_BOX - 8) / 4) {
                    const int zn = clock_after(old) - old * TUNED(TAU) / 128 + (vid >> 4) * TUNED(STAG);
                    z = prev && zn - z < TUNED(JUMP) ? z + ((zn - z) >> TUNED(GAIN)) : zn;
                    prev = old;
                    sts_volatile2(sbase + OFF_WIN, 4 * old < tiles4(4 * TUNED(IMIN)) ? TUNED(WMIN0) : TUNED(WMIN), z);
                }
            }
            t1 = now;
        } else {
            __nanosleep(TUNED(SVC));
        }
        last = pos;
        if (spins > SPIN_LIMIT) __trap();
    }
}

__device__ __forceinline__ void softmax_A(const Params& p, char* smem, int w, int lane, int ab, int asp) {
    const int mat = lane >> 3, r = lane & 7;
    float m_run[4], l_run[4];
#pragma unroll
    for (int i = 0; i < 4; i++) { m_run[i] = -INFINITY; l_run[i] = 0.f; }
    const float* red = (const float*)(smem + OFF_ARED);
    for (int k = 0; k < ATILES; k++) {
        bar_sync(BAR_R, 352);
        float4 s[4];
        float mt[4];
#pragma unroll
        for (int i = 0; i < 4; i++) {
            const float* src = red + (16 * w + 4 * i + mat) * 40 + 4 * r;
            const float4 a = *(const float4*)src, b = *(const float4*)(src + 32 * 40);
            const float4 c = *(const float4*)(src + 64 * 40), d = *(const float4*)(src + 96 * 40);
            const uint32_t v0 = score_round2((a.x + b.x) + (c.x + d.x), (a.y + b.y) + (c.y + d.y));
            const uint32_t v1 = score_round2((a.z + b.z) + (c.z + d.z), (a.w + b.w) + (c.w + d.w));
            s[i] = make_float4(bf_lo(v0), bf_hi(v0), bf_lo(v1), bf_hi(v1));
            mt[i] = fmaxf(fmaxf(s[i].x, s[i].y), fmaxf(s[i].z, s[i].w));
        }
#pragma unroll
        for (int o = 1; o < 8; o <<= 1)
#pragma unroll
            for (int i = 0; i < 4; i++) mt[i] = fmaxf(mt[i], __shfl_xor_sync(0xffffffffu, mt[i], o));
#pragma unroll
        for (int i = 0; i < 4; i++) {
            const int head = 16 * w + 4 * i + mat;
            const float m_new = fmaxf(m_run[i], mt[i]);
            const float al = ex2((m_run[i] - m_new) * LOG2E);
            const float e0 = ex2((s[i].x - m_new) * LOG2E), e1 = ex2((s[i].y - m_new) * LOG2E);
            const float e2 = ex2((s[i].z - m_new) * LOG2E), e3 = ex2((s[i].w - m_new) * LOG2E);
            l_run[i] = l_run[i] * al + (e0 + e1) + (e2 + e3);
            m_run[i] = m_new;
            *(uint2*)(smem + OFF_AP + (k & 1) * 2560 + head * 80 + r * 8) = make_uint2(pack_bf16(e0, e1), pack_bf16(e2, e3));
            if (r == 0) ((float*)(smem + OFF_AALPHA))[(k & 1) * 32 + head] = al;
        }
        bar_arrive(BAR_P, 320);
    }
#pragma unroll
    for (int i = 0; i < 4; i++) {
        float l = l_run[i];
        l += __shfl_xor_sync(0xffffffffu, l, 1);
        l += __shfl_xor_sync(0xffffffffu, l, 2);
        l += __shfl_xor_sync(0xffffffffu, l, 4);
        if (r == 0) p.sc->ml[((16 * w + 4 * i + mat) * SPLIT + asp) * 4 + ab] = make_float2(m_run[i], l);
    }
    bar_arrive(BAR_E, 320);
}

__device__ __forceinline__ void attention_A(const Params& p, char* smem, int sw, int lane, int ab, int asp) {
    const uint32_t sbase = smem_u32(smem);
    const int tid = sw * 32 + lane;
    const int g = lane >> 2, t = lane & 3, mat = lane >> 3, r = lane & 7;
    const int mi = sw & 1, cq = sw >> 1;
    uint4 qf[8];
    {
        const unsigned* src = p.sc->qabs + ab * 8192 + sw * 1024 + lane * 4;
        for (int k = 0; k < TUNED(ASLEEP); k++) __nanosleep(1000);
        ll_poll4(qf, src, 128, 500);
        if (sw == 0) PROF(6);
    }
    bar_sync(BAR_S, NSW * 32);
    float oacc[2][8][4];
#pragma unroll
    for (int a = 0; a < 2; a++)
#pragma unroll
        for (int b = 0; b < 8; b++) zero4(oacc[a][b]);
    float* red = (float*)(smem + OFF_ARED) + (cq * 32 + 16 * mi + g) * 40 + 2 * t;
    const uint32_t qk_off = sbase + 2 * cq * 4096 + ((mat >> 1) * 8 + r) * 128 + (((mat & 1) ^ r) << 4);
    const uint32_t pv_off = sbase + sw * 4096 + ((mat & 1) * 8 + r) * 128 + (((mat >> 1) ^ r) << 4);
    const uint32_t p_off = sbase + OFF_AP + ((mat & 1) * 8 + r) * 80 + (mat >> 1) * 16;
    int st = 0, ph = 0, stp = 0;
    for (int k = -1; k < ATILES; k++) {
        float sacc[4][4];
        if (k + 1 < ATILES) {
            mbar_wait(sbase + OFF_BAR + (MB_AFULL + st) * 8, ph);
            if (k == -1 && sw == 0) PROF(13);
#pragma unroll
            for (int a = 0; a < 4; a++) zero4(sacc[a]);
#pragma unroll
            for (int ks = 0; ks < 8; ks++) {
#pragma unroll
                for (int np = 0; np < 2; np++) {
                    uint32_t b0, b1, b2, b3;
                    ldsm4(b0, b1, b2, b3, (qk_off ^ ((ks & 3) << 5)) + st * 32768 + (ks >> 2) * 4096 + np * 2048);
                    mma(sacc[2 * np], qf[ks].x, qf[ks].y, qf[ks].z, qf[ks].w, b0, b1);
                    mma(sacc[2 * np + 1], qf[ks].x, qf[ks].y, qf[ks].z, qf[ks].w, b2, b3);
                }
            }
        }
        if (k >= 0) bar_sync(BAR_P, 320);
        if (k + 1 < ATILES) {
#pragma unroll
            for (int nt = 0; nt < 4; nt++) {
                *(float2*)(red + 8 * nt) = make_float2(sacc[nt][0], sacc[nt][1]);
                *(float2*)(red + 8 * nt + 8 * 40) = make_float2(sacc[nt][2], sacc[nt][3]);
            }
            bar_arrive(BAR_R, 352);
        }
        if (k >= 0) {
            const float* alpha = (const float*)(smem + OFF_AALPHA) + (k & 1) * 32;
            const float al0 = alpha[g], al1 = alpha[g + 8], al2 = alpha[g + 16], al3 = alpha[g + 24];
            if (!__all_sync(0xffffffffu, al0 == 1.f && al1 == 1.f && al2 == 1.f && al3 == 1.f)) {
#pragma unroll
                for (int nt = 0; nt < 8; nt++) {
                    oacc[0][nt][0] *= al0; oacc[0][nt][1] *= al0; oacc[0][nt][2] *= al1; oacc[0][nt][3] *= al1;
                    oacc[1][nt][0] *= al2; oacc[1][nt][1] *= al2; oacc[1][nt][2] *= al3; oacc[1][nt][3] *= al3;
                }
            }
#pragma unroll
            for (int ks = 0; ks < 2; ks++) {
                uint32_t pa[2][4];
#pragma unroll
                for (int mt = 0; mt < 2; mt++)
                    ldsm4(pa[mt][0], pa[mt][1], pa[mt][2], pa[mt][3], p_off + (k & 1) * 2560 + mt * 16 * 80 + ks * 32);
#pragma unroll
                for (int np = 0; np < 4; np++) {
                    uint32_t b0, b1, b2, b3;
                    ldsm4t(b0, b1, b2, b3, (pv_off ^ (np << 5)) + stp * 32768 + ks * 2048);
#pragma unroll
                    for (int mt = 0; mt < 2; mt++) {
                        mma(oacc[mt][2 * np], pa[mt][0], pa[mt][1], pa[mt][2], pa[mt][3], b0, b1);
                        mma(oacc[mt][2 * np + 1], pa[mt][0], pa[mt][1], pa[mt][2], pa[mt][3], b2, b3);
                    }
                }
            }
        }
        stp = st;
        if (++st == ASTAGES) { st = 0; ph ^= 1; }
    }
    if (sw == 0) PROF(14);
    {
        float dep = 0.f;
#pragma unroll
        for (int nt = 0; nt < 8; nt++) dep += oacc[1][nt][0];
        warp_release(sbase + OFF_BAR + MB_F3 * 8, lane, dep);
    }
#pragma unroll
    for (int mt = 0; mt < 2; mt++)
#pragma unroll
        for (int hh = 0; hh < 2; hh++) {
            float4* op = (float4*)(p.sc->opart + ((16 * mt + 8 * hh + g) * SPLIT + asp) * 2048 + sw * 256 + ab * 64) + t;
#pragma unroll
            for (int q = 0; q < 4; q++)
                op[4 * q] = make_float4(oacc[mt][2 * q][2 * hh], oacc[mt][2 * q][2 * hh + 1],
                                    oacc[mt][2 * q + 1][2 * hh], oacc[mt][2 * q + 1][2 * hh + 1]);
        }
    bar_sync(BAR_E, 320);
    if (tid == 0) signal_counter(&p.sc->cnt);
    if (sw == 0) PROF(7);
}

__device__ __forceinline__ float matvec64(char* smem, const uint32_t (&xf)[4][2], int mb_full, int mb_free, int sw, int lane) {
    const uint32_t sbase = smem_u32(smem);
    const int g = lane >> 2, t = lane & 3, mat = lane >> 3, r = lane & 7;
    const uint32_t a = sbase + BLK_W + sw * 8192 + ((mat >> 1) * 8 + r) * 128 + (((mat & 1) ^ r) << 4);
    float c[4][4];
#pragma unroll
    for (int mt = 0; mt < 4; mt++) zero4(c[mt]);
    mbar_wait(sbase + OFF_BAR + (mb_full + (sw >> 1)) * 8, 0);
#pragma unroll
    for (int ks = 0; ks < 4; ks++)
#pragma unroll
        for (int mt = 0; mt < 4; mt++) {
            uint32_t a0, a1, a2, a3;
            ldsm4t(a0, a1, a2, a3, (a ^ (mt << 5)) + ks * 2048);
            mma(c[mt], a0, a1, a2, a3, xf[ks][0], xf[ks][1]);
        }
    warp_release(sbase + OFF_BAR + mb_free * 8, lane, (c[0][0] + c[1][0]) + (c[2][0] + c[3][0]));
    float* rp = (float*)(smem + OFF_RED);
#pragma unroll
    for (int mt = 0; mt < 4; mt++) {
        const float y0 = (t < 2 ? c[mt][0] : c[mt][2]) + __shfl_xor_sync(0xffffffffu, t < 2 ? c[mt][2] : c[mt][0], 2);
        const float y1 = (t < 2 ? c[mt][1] : c[mt][3]) + __shfl_xor_sync(0xffffffffu, t < 2 ? c[mt][3] : c[mt][1], 2);
        float* d = rp + sw * 256 + (t & 1) * 128 + 16 * mt + (t >> 1) * 8 + g;
        d[0] = y0;
        d[64] = y1;
    }
    bar_sync(BAR_S, NSW * 32);
    float y = 0.f;
#pragma unroll
    for (int i = 0; i < NSW; i++) y += rp[i * 256 + sw * 32 + lane];
    return y;
}
__device__ __forceinline__ void load_xfrags(const char* smem, uint32_t (&xf)[4][2], int sw, int lane) {
    const uint32_t* x32 = (const uint32_t*)(smem + OFF_X) + ((lane >> 2) & 3) * 256 + 32 * sw + (lane & 3);
#pragma unroll
    for (int ks = 0; ks < 4; ks++) {
        xf[ks][0] = lane < 16 ? x32[ks * 8] : 0u;
        xf[ks][1] = lane < 16 ? x32[ks * 8 + 4] : 0u;
    }
}
__device__ __forceinline__ int vec_word(int vid, int tid) { return (tid >> 6) * 2048 + (vid >> 1) * 32 + ((tid & 63) >> 1); }
__device__ __forceinline__ void store_vec(unsigned* dst, int vid, int tid, float y) {
    const float y1 = __shfl_down_sync(0xffffffffu, y, 1);
    if (!(tid & 1)) ll_store(dst + vec_word(vid, tid), pack_bf16(y, y1));
}
__device__ __forceinline__ void fill_qtab(const Params& p, char* smem, bool isA, int vid, int tid) {
    static_assert(R_LATE == 17, "rows");
    const int r = max(1 + (tid >> 4), isA ? R_JOIN : 0), pair = chunk_of(r, vid) >> 4;
    uint4 v[2];
    ll_poll4(v, p.sc->qB + pair * 64 + (tid & 15) * 4, (late_pair(vid) - pair) * 64, 300);
    *(uint4*)(smem + OFF_Q + 256 + tid * 16) = v[0];
    if (tid < 16) *(uint4*)(smem + OFF_Q + R_LATE * 256 + tid * 16) = v[1];
    __syncwarp();
    if ((tid & 31) == 0) mbar_expect_tx(smem_u32(smem) + OFF_BAR + MB_Q * 8, 0);
}
__device__ __forceinline__ void clear_handoffs(const Params& p, int vid, int tid) {
    const int chunk = chunk_of(R_LATE, vid);
    if (tid < 32) *(uint4*)(p.sc->part + chunk * 128 + tid * 4) = make_uint4(0, 0, 0, 0);
    if (tid == 32) *(uint2*)(p.sc->pml + chunk * 2) = make_uint2(0, 0);
    if ((tid >> 4) == 4 && vid < N_EARLY) *(uint4*)(p.sc->oB + vid * 64 + (tid & 15) * 4) = make_uint4(0, 0, 0, 0);
    if ((tid >> 2) == 24) *(uint4*)(p.out + vid * 32 + (tid & 3) * 8) = make_uint4(0, 0, 0, 0);
    if (!((vid | tid) & 1)) p.sc->ctx[vec_word(vid, tid)] = 0;
}
__device__ __forceinline__ void side_prologue(const Params& p, char* smem, bool isA, int vid, int sw, int lane) {
    const uint32_t sbase = smem_u32(smem);
    const uint32_t bars = sbase + OFF_BAR;
    const int h = vid & 31, j = vid >> 5;
    const int tid = sw * 32 + lane;
    const int g = lane >> 2, t = lane & 3, mat = lane >> 3, r = lane & 7;
    {
        uint32_t xf[4][2];
        mbar_wait(bars + MB_X * 8, 0);
        load_xfrags(smem, xf, sw, lane);
        if (sw == 0) PROF(16);
        store_vec((vid & 1) ? p.sc->qA : p.sc->qB, vid, tid, matvec64(smem, xf, MB_SIDE + SI_WQ, MB_F0, sw, lane));
        if (sw == 0) PROF(18);
    }
    if (tid == 255) asm volatile("fence.acq_rel.gpu;" ::: "memory");
    __syncwarp();
    __nanosleep(TUNED(GSLEEP));
    if (tid < 64) {
        uint4 v[1];
        ll_poll4(v, p.sc->qA + (tid >> 4) * 2048 + h * 64 + (tid & 15) * 4, 0, 300);
        *(uint4*)(smem + OFF_VEC + (tid >> 4) * 272 + (tid & 15) * 16) = v[0];
    }
    fill_qtab(p, smem, isA, vid, tid);
    bar_sync(BAR_S, NSW * 32);
    if (sw == 0) PROF(21);
    {
        mbar_wait(bars + (MB_SIDE + SI_WUK) * 8, 0);
        mbar_wait(bars + (MB_SIDE + SI_WUK + 1) * 8, 0);
        float c2[2][4];
        zero4(c2[0]); zero4(c2[1]);
        const uint32_t* qa = (const uint32_t*)(smem + OFF_VEC + (g & 3) * 272) + t;
        const uint32_t a = sbase + BLK_U + sw * 2048 + ((mat >> 1) * 8 + r) * 128 + (((mat & 1) ^ r) << 4);
#pragma unroll
        for (int ks = 0; ks < 8; ks++) {
            uint32_t b0, b1, b2, b3;
            ldsm4(b0, b1, b2, b3, (a ^ ((ks & 3) << 5)) + (ks >> 2) * 16384);
            const uint32_t a0 = qa[ks * 8], a2 = qa[ks * 8 + 4];
            mma(c2[0], a0, 0, a2, 0, b0, b1);
            mma(c2[1], a0, 0, a2, 0, b2, b3);
        }
        warp_release(bars + MB_FU * 8, lane, c2[0][0] + c2[1][0]);
        ll_store(p.sc->qabs + qabs_word(g & 3, h, j, sw, g >> 2, t),
                 g < 4 ? pack_bf16(c2[0][0], c2[0][1]) : pack_bf16(c2[1][0], c2[1][1]));
    }
    if (sw == 0) PROF(5);
}

__device__ __forceinline__ void side_epilogue(const Params& p, char* smem, bool isA, int vid, int sw, int lane) {
    const uint32_t sbase = smem_u32(smem);
    const uint32_t bars = sbase + OFF_BAR;
    const int tid = sw * 32 + lane;
    const int g = lane >> 2, t = lane & 3;
    mbar_wait(bars + MB_CNT * 8, 0);
    if (sw == 0) PROF(8);
    if (!(vid & 1)) {
        uint32_t of[4][2];
        const int h = vid >> 2;
        const int b = g & 3, sp = g >> 2;
        float wgt[SPLIT / 2];
        {
            float2 ml[SPLIT / 2];
            float M = -INFINITY, L = 0.f;
#pragma unroll
            for (int q = 0; q < SPLIT / 2; q++) { ml[q] = __ldcg(&p.sc->ml[(h * SPLIT + sp + 2 * q) * 4 + b]); M = fmaxf(M, ml[q].x); }
            M = fmaxf(M, __shfl_xor_sync(0xffffffffu, M, 16));
#pragma unroll
            for (int q = 0; q < SPLIT / 2; q++) { wgt[q] = ex2((ml[q].x - M) * LOG2E); L = fmaf(wgt[q], ml[q].y, L); }
            L += __shfl_xor_sync(0xffffffffu, L, 16);
#pragma unroll
            for (int q = 0; q < SPLIT / 2; q++) { wgt[q] /= L; mbar_wait(bars + (MB_SIDE + SI_OPART + q) * 8, 0); }
        }
#pragma unroll
        for (int ks = 0; ks < 4; ks++) {
            float v[4] = {0.f, 0.f, 0.f, 0.f};
#pragma unroll
            for (int q = 0; q < SPLIT / 2; q++) {
                const float4 u = *((const float4*)(smem + BLK_U) + (sp + 2 * q) * 512 + sw * 64 + b * 16 + 4 * ks + t);
                v[0] = fmaf(u.x, wgt[q], v[0]); v[1] = fmaf(u.y, wgt[q], v[1]);
                v[2] = fmaf(u.z, wgt[q], v[2]); v[3] = fmaf(u.w, wgt[q], v[3]);
            }
#pragma unroll
            for (int e = 0; e < 4; e++) v[e] += __shfl_xor_sync(0xffffffffu, v[e], 16);
#pragma unroll
            for (int hh = 0; hh < 2; hh++) {
                const uint32_t hi = pack_bf16(v[2 * hh], v[2 * hh + 1]);
                of[ks][hh] = sp == 0 ? hi : pack_bf16(v[2 * hh] - bf_lo(hi), v[2 * hh + 1] - bf_hi(hi));
            }
        }
        store_vec(p.sc->ctx, vid, tid, matvec64(smem, of, MB_SIDE + SI_WE, MB_F2, sw, lane));
        if (sw == 0) PROF(9);
    }
    const bool isB = !(vid & 1), late = isB && tid >= 240;
    const unsigned* xs = (isB ? p.sc->oB : p.sc->ctx) + (tid >> 4) * 512 + (vid >> 4) * 64 + (tid & 15) * 4;
    const uint32_t xa = sbase + OFF_X + t * (4 * XROW) + (lane & 8) * 4 + (lane & 16);
    const uint32_t wa = sbase + BLK_W + lane * 128 + ((sw ^ (lane & 7)) << 4);
    const int il = I_LAST - (isA ? 8 * R_JOIN : 0), sl = il % NS;
    const uint32_t va = sbase + OFF_RING + sl * TILE_BYTES + (sw >> 2) * 8192 + ((lane >> 4) * 8 + (lane & 7)) * 128 + (((2 * (sw & 3) + (g >> 1 & 1)) ^ (lane & 7)) << 4);
    uint32_t* out = (uint32_t*)(p.out + (g & 3) * 1024 + (isB ? 512 : 0) + ((vid >> 1) & 7) * 64 + 8 * sw) + t;
    unsigned* lp = p.sc->part + late_pair(vid) * 2048 + 16 * sw;
    unsigned* lm = p.sc->pml + late_pair(vid) * 32;
    const uint4* lf = (const uint4*)(smem + OFF_X + 4 * (3 * XROW + 192)) + t;
    __nv_bfloat16* lx = (__nv_bfloat16*)(smem + OFF_X) + 2 * (3 * XROW + 192) + 32 * (sw >> 1) + 16 * (t & 1) + ((lane & 16) >> 1) +
                        2 * (t & 2) + 2 * (sw & 1) + ((lane >> 3) & 1);
#pragma unroll 1
    for (int pass = 0; pass < 2; pass++) {
        const uint32_t wo = bars + (pass ? MB_SIDE + SI_WO : MB_X) * 8, vf = bars + (pass ? MB_FULL + sl : MB_X) * 8;
        uint4 v = make_uint4(1, 1, 1, 1), u0 = v, u1 = v;
        uint2 m0 = make_uint2(1, 1), m1 = m0;
        {
            mbar_wait(bars + (pass ? MB_PH : MB_CNT) * 8, 0);
            const float4 ma = *(const float4*)(smem + OFF_MLO), mb = *(const float4*)(smem + OFF_MLO + 16);
            const float M = fmaxf(fmaxf(ma.x, ma.z), fmaxf(mb.x, mb.z));
            const float a[4] = {ex2((ma.x - M) * LOG2E), ex2((ma.z - M) * LOG2E), ex2((mb.x - M) * LOG2E), ex2((mb.z - M) * LOG2E)};
            if (pass && tid == 0)
                ll_store2(lm + 2 * (vid & 15), __float_as_uint(M), __float_as_uint((a[0] * ma.y + a[1] * ma.w) + (a[2] * mb.y + a[3] * mb.w)));
            const int done = lds_volatile(sbase + OFF_DONE);
            float f = 0.f;
#pragma unroll
            for (int u = 0; u < 4; u++) {
                const uint4 p0 = *(const uint4*)(smem + OFF_PH + u * 128 + t * 32), p1 = *(const uint4*)(smem + OFF_PH + u * 128 + t * 32 + 16);
                const uint32_t pb[4][2] = {{p0.x, p0.y}, {p0.z, p0.w}, {p1.x, p1.y}, {p1.z, p1.w}};
                float c[4][4];
                mbar_wait(vf + u * 8, pass & (il / NS));
                if (sw == 0) PROF(u < 2 ? 19 + u : u);
#pragma unroll
                for (int k = 0; k < 4; k++) {
                    uint32_t a0, a1, a2, a3;
                    ldsm4t(a0, a1, a2, a3, va + u * TILE_BYTES + k * 2048);
                    zero4(c[k]);
                    mma(c[k], a0, a1, a2, a3, pb[k][0], pb[k][1]);
                }
                const float f0 = (c[0][0] + c[1][0]) + (c[2][0] + c[3][0]), f1 = (c[0][2] + c[1][2]) + (c[2][2] + c[3][2]);
                f = fmaf(a[u], (t & 1) ? f1 : f0, f);
                if (u == 3 && pass && t < 2) ll_store(lp + (vid & 15) * 128 + 8 * t + g, __float_as_uint(f));
                if (pass && tid == 0) sts_volatile(sbase + OFF_DONE, done + u + 1);
                if (u == TUNED(GO) && pass) {
                    if (!late) v = ll_load4(xs);
                    if (isB) { m0 = ll_load2(lm + 2 * g); m1 = ll_load2(lm + 2 * g + 16); }
                }
            }
            if (sw == 0) PROF(10);
        }
        for (unsigned spins = 0; !(ll_ok4(v) && ll_ok4(make_uint4(m0.x, m0.y, m1.x, m1.y))); spins++) {
            __nanosleep(200);
            if (!late) v = ll_load4(xs);
            if (isB) { m0 = ll_load2(lm + 2 * g); m1 = ll_load2(lm + 2 * g + 16); }
            if (spins > SPIN_LIMIT) __trap();
        }
        __syncwarp();
        if (!late) *(uint4*)(smem + OFF_X + (tid >> 6) * (4 * XROW) + (tid & 63) * 16) = make_uint4(~v.x, ~v.y, ~v.z, ~v.w);
        bar_sync(BAR_S, NSW * 32);
        if (sw == 0) PROF(15);
        float w0, w1;
        {
            const float a0 = __uint_as_float(~m0.x), a1 = __uint_as_float(~m1.x), M = redux_max(fmaxf(a0, a1));
            w0 = ex2((a0 - M) * LOG2E), w1 = ex2((a1 - M) * LOG2E);
            float l = w0 * __uint_as_float(~m0.y) + w1 * __uint_as_float(~m1.y);
#pragma unroll
            for (int k = 4; k < 32; k <<= 1) l += __shfl_xor_sync(0xffffffffu, l, k);
            w0 = __fdividef(w0, l), w1 = __fdividef(w1, l);
            if (pass && sw == 0 && !(vid & 15)) *(uint2*)(p.sc->qB + late_pair(vid) * 64 + 2 * lane) = make_uint2(0, 0);
        }
        float acc[4][4];
#pragma unroll
        for (int k = 0; k < 4; k++) zero4(acc[k]);
        uint32_t xf[4][4][4], b[4][4];
        auto rows = [&](int q) {
#pragma unroll
            for (int k = 0; k < 4; k++) ldsm4(xf[q][k][0], xf[q][k][1], xf[q][k][2], xf[q][k][3], xa + q * 256 + k * 64);
        };
        auto load = [&](int q, int h) {
#pragma unroll
            for (int k = 2 * h; k < 2 * h + 2; k++) ldsm4t(b[k][0], b[k][1], b[k][2], b[k][3], wa + q * TILE_BYTES + k * 4096);
        };
        auto mult = [&](int q) {
#pragma unroll
            for (int k = 0; k < 8; k++)
                mma(acc[k & 3], xf[q][k >> 1][0], xf[q][k >> 1][1], xf[q][k >> 1][2], xf[q][k >> 1][3], b[k >> 1][2 * (k & 1)], b[k >> 1][2 * (k & 1) + 1]);
        };
        rows(0); rows(1); rows(2); rows(3);
        mbar_wait(wo, 0);
        load(0, 0); load(0, 1); mult(0);
        if (isB) {
            const int z = lds_volatile(sbase + OFF_WIN + 4) + tiles4(TUNED(TRIG)) * TUNED(TAU) / 512;
            for (int k = pass ? 0 : 63; k < 64 && !__any_sync(0xffffffffu, (int)(now_ns() - z) >= 0); k++) __nanosleep(20);
            if (sw == 0) PROF(27);
            if (pass) { u0 = ll_load4(lp + g * 128 + 4 * t); u1 = ll_load4(lp + g * 128 + 4 * t + 1024); }
        }
        mbar_wait(wo + 8, 0);
        load(1, 0); load(1, 1); mult(1);
        if (isB) {
            for (unsigned spins = 0; !__all_sync(0xffffffffu, ll_ok4(u0) && ll_ok4(u1)); spins++) {
                if (sw == 0 && spins < 3) PROF2(150 + spins);
                u0 = ll_load4(lp + g * 128 + 4 * t); u1 = ll_load4(lp + g * 128 + 4 * t + 1024);
                if (spins > SPIN_LIMIT) __trap();
            }
            if (sw == 0) PROF2(153);
            const float o0 = w0 * __uint_as_float(~u0.x) + w1 * __uint_as_float(~u1.x), o1 = w0 * __uint_as_float(~u0.y) + w1 * __uint_as_float(~u1.y);
            const float o2 = w0 * __uint_as_float(~u0.z) + w1 * __uint_as_float(~u1.z), o3 = w0 * __uint_as_float(~u0.w) + w1 * __uint_as_float(~u1.w);
            const bool hi = lane & 16, mid = lane & 8;
            const float e0 = (hi ? o2 : o0) + __shfl_xor_sync(0xffffffffu, hi ? o0 : o2, 16);
            const float e1 = (hi ? o3 : o1) + __shfl_xor_sync(0xffffffffu, hi ? o1 : o3, 16);
            const float e = (mid ? e1 : e0) + __shfl_xor_sync(0xffffffffu, mid ? e0 : e1, 8);
            *lx = __float2bfloat16_rn(e + __shfl_xor_sync(0xffffffffu, e, 4));
            if (sw == 0) PROF(4);
        }
        bool r2 = mbar_test(wo + 16, 0);
        if (isB) bar_sync(BAR_S, NSW * 32);
        if (isB && g == 3) {
#pragma unroll
            for (int k = 0; k < 4; k++) {
                const uint4 f = lf[4 * k];
                xf[3][k][0] = f.x; xf[3][k][1] = f.y; xf[3][k][2] = f.z; xf[3][k][3] = f.w;
            }
        }
        mbar_wait_unless(r2, wo + 16);
        bool r3 = mbar_test(wo + 24, 0);
        load(2, 0); load(2, 1); mult(2);
        mbar_wait_unless(r3, wo + 24);
        r3 = mbar_try(wo + 32, 0);
        load(3, 0);
        mbar_wait_unless(r3, wo + 32);
        if (sw == 0) PROF(11);
        load(3, 1); mult(3);
        const uint32_t y = pack_bf16((acc[0][0] + acc[1][2]) + (acc[2][0] + acc[3][2]), (acc[0][1] + acc[1][3]) + (acc[2][1] + acc[3][3]));
        asm volatile("{\n .reg .pred q;\n setp.ne.u32 q, %2, 0;\n @q red.relaxed.gpu.global.add.noftz.bf16x2 [%0], %1;\n}"
                     ::"l"(out), "r"(y), "r"((int)(pass && lane < 16)) : "memory");
    }
    if (sw == 7) PROF(25);
    if (sw == 2) PROF(24);
}

__global__ void __launch_bounds__(NTHREADS, 1) fused_decode_kernel(const Ptrs ptrs, const __grid_constant__ Maps maps) {
    extern __shared__ __align__(1024) char smem[];
    Params p;
    static_cast<Ptrs&>(p) = ptrs;
    p.tm = maps.tm;
    const unsigned blk = blockIdx.x;
    asm volatile("{\n .reg .u64 a;\n mad.wide.u32 a, %1, 32, %0;\n prefetch.global.L2 [a];\n}" ::"l"(p.K), "r"(blk * NTHREADS + threadIdx.x) : "memory");
    if (threadIdx.x == 0) first_load(p, smem_u32(smem), blk);
    const int warp = __shfl_sync(0xffffffffu, threadIdx.x >> 5, 0), lane = threadIdx.x & 31;
    const bool isA = blk % APER == APER - 1;
    const int aidx = blk / APER, ab = aidx / SPLIT, asp = aidx % SPLIT;
    const int vid = isA ? NB + aidx : blk - aidx;
    if (threadIdx.x == 32) next_loads(p, smem_u32(smem), vid);
    if (lane == 0 && warp != 1) {
        const int wu = max(warp, 1);
#pragma unroll
        for (int k = 0; k < (MB_COUNT - MB_EARLY + 10) / 11; k++) {
            const int i = MB_EARLY + k * 11 + wu - 1;
            if (i < MB_COUNT && i != MB_FULL) mbar_init(smem_u32(smem) + OFF_BAR + i * 8, i >= MB_F0 ? NSW : i == MB_PH ? 4 : 1);
        }
        fence_mbar_init();
        if (wu >= 2 && wu < 8) asm volatile("prefetch.tensormap [%0];" ::"l"(&p.tm[wu]) : "memory");
    }
    __syncwarp();
    if (threadIdx.x == 33) {
        *(int2*)(smem + OFF_DONE) = make_int2(0, 0);
        *(int2*)(smem + OFF_WIN) = make_int2(TUNED(WSTART), 0);
    }
    if (warp >= 4) clear_handoffs(p, vid, threadIdx.x - 128);
    bar_sync(0, NTHREADS);
    if (warp == 0) {
        produce(p, smem, lane, isA, vid, ab * 4096 + asp * 32);
    } else if (warp < 3) {
        if (isA) softmax_A(p, smem, warp - 1, lane, ab, asp);
        consume(p, smem, isA, vid, warp - 1, lane);
    } else if (warp == 3) {
        service(p, smem, isA, vid, lane);
    } else {
        const int sw = warp - 4;
        side_prologue(p, smem, isA, vid, sw, lane);
        if (isA) attention_A(p, smem, sw, lane, ab, asp);
        side_epilogue(p, smem, isA, vid, sw, lane);
    }
}

__device__ float g_tmp[2][4 * 32 * 512];
__device__ __forceinline__ float bfr(float x) { return __bfloat162float(__float2bfloat16_rn(x)); }
template <typename X>
__global__ void fb_matvec(const X* x, int xb, int xh, int K, const __nv_bfloat16* W, int wk, int wh, int wn, float* y,
                          __nv_bfloat16* out, bool round) {
    const int n = threadIdx.x, h = blockIdx.x, b = blockIdx.y;
    float s = 0.f;
    for (int k = 0; k < K; k++) s += (float)x[b * xb + h * xh + k] * __bfloat162float(W[(size_t)k * wk + h * wh + (size_t)n * wn]);
    if (out) out[b * 1024 + n] = __float2bfloat16_rn(s);
    else y[(b * gridDim.x + h) * blockDim.x + n] = round ? bfr(s) : s;
}
__global__ void fb_attn(const float* q, const __nv_bfloat16* K, const __nv_bfloat16* V, int D, size_t sb, size_t sh, float* o, bool round) {
    __shared__ float sc[4096], red[8];
    const int h = blockIdx.x, b = blockIdx.y, tid = threadIdx.x;
    K += b * sb + h * sh; V += b * sb + h * sh; q += (b * 32 + h) * D;
    float m = -INFINITY, l = 0.f;
    for (int k = tid; k < 4096; k += 256) {
        float s = 0.f;
        for (int d = 0; d < D; d++) s += q[d] * __bfloat162float(K[(size_t)k * D + d]);
        m = fmaxf(m, sc[k] = bfr(bfr(s) * SCALE));
    }
    m = warp_max(m);
    if (!(tid & 31)) red[tid >> 5] = m;
    __syncthreads();
    for (int i = 0; i < 8; i++) m = fmaxf(m, red[i]);
    __syncthreads();
    for (int k = tid; k < 4096; k += 256) { const float e = expf(sc[k] - m); l += e; sc[k] = bfr(e); }
    l = warp_sum(l);
    if (!(tid & 31)) red[tid >> 5] = l;
    __syncthreads();
    l = 0.f;
    for (int i = 0; i < 8; i++) l += red[i];
    for (int d = tid; d < D; d += 256) {
        float s = 0.f;
        for (int k = 0; k < 4096; k++) s += sc[k] * __bfloat162float(V[(size_t)k * D + d]);
        o[(b * 32 + h) * D + d] = round ? bfr(s / l) : s / l;
    }
}
void launch_fallback(void* const* d_in, __nv_bfloat16* out) {
    typedef const __nv_bfloat16* BP;
    float* t0;
    cudaGetSymbolAddress((void**)&t0, g_tmp);
    float* t1 = t0 + 4 * 32 * 512;
    const dim3 gh(32, 4), g1(1, 4);
    fb_matvec<<<gh, 128>>>((BP)d_in[0], 512, 0, 512, (BP)d_in[2], 4096, 128, 1, t0, nullptr, true);
    fb_matvec<<<gh, 512>>>((const float*)t0, 4096, 128, 128, (BP)d_in[3], 1, 128, 4096, t1, nullptr, true);
    fb_attn<<<gh, 256>>>(t1, (BP)d_in[1], (BP)d_in[1], 512, (size_t)4096 * 512, 0, t0, false);
    fb_matvec<<<gh, 128>>>((const float*)t0, 32 * 512, 512, 512, (BP)d_in[4], 4096, 128, 1, t1, nullptr, true);
    fb_matvec<<<g1, 512>>>((const float*)t1, 4096, 0, 4096, (BP)d_in[5], 512, 0, 1, nullptr, out, false);
    fb_matvec<<<gh, 128>>>((BP)d_in[6], 512, 0, 512, (BP)d_in[9], 4096, 128, 1, t0, nullptr, true);
    fb_attn<<<gh, 256>>>(t0, (BP)d_in[7], (BP)d_in[8], 128, (size_t)32 * 4096 * 128, (size_t)4096 * 128, t1, true);
    fb_matvec<<<g1, 512>>>((const float*)t1, 4096, 0, 4096, (BP)d_in[10], 512, 0, 1, nullptr, out + 512, false);
}

typedef CUresult (*EncodeFn)(CUtensorMap*, CUtensorMapDataType, cuuint32_t, void*, const cuuint64_t*, const cuuint64_t*,
                             const cuuint32_t*, const cuuint32_t*, CUtensorMapInterleave, CUtensorMapSwizzle,
                             CUtensorMapL2promotion, CUtensorMapFloatOOBfill);

void make_map(EncodeFn enc, CUtensorMap* tm, void* ptr, uint64_t cols, uint64_t rows, uint32_t br) {
    const cuuint64_t dims[2] = {cols, rows};
    const cuuint64_t strides[1] = {cols * 2};
    const cuuint32_t box[2] = {64, br};
    const cuuint32_t es[2] = {1, 1};
    enc(tm, CU_TENSOR_MAP_DATA_TYPE_BFLOAT16, 2, ptr, dims, strides, box, es, CU_TENSOR_MAP_INTERLEAVE_NONE,
        CU_TENSOR_MAP_SWIZZLE_128B, CU_TENSOR_MAP_L2_PROMOTION_NONE,
        CU_TENSOR_MAP_FLOAT_OOB_FILL_NONE);
}

}

extern "C" void kernel_launch(void* const* d_in, const int* in_sizes, int n_in, void* d_out, int out_size) {
    (void)in_sizes; (void)n_in; (void)out_size;
    void* fn = nullptr;
    cudaDriverEntryPointQueryResult qr;
    cudaGetDriverEntryPoint("cuTensorMapEncodeTiled", &fn, cudaEnableDefault, &qr);
    EncodeFn enc = (EncodeFn)fn;
    int dev = 0, sms = 0, per_sm = 0;
    cudaGetDevice(&dev);
    cudaDeviceGetAttribute(&sms, cudaDevAttrMultiProcessorCount, dev);
    cudaFuncSetAttribute(fused_decode_kernel, cudaFuncAttributeMaxDynamicSharedMemorySize, SMEM_BYTES);
    cudaOccupancyMaxActiveBlocksPerMultiprocessor(&per_sm, fused_decode_kernel, NTHREADS, SMEM_BYTES);
    if (!enc || sms * per_sm < NCTA) {
        launch_fallback(d_in, (__nv_bfloat16*)d_out);
        return;
    }
    Ptrs p;
    Maps m;
    make_map(enc, &m.tm[0], d_in[9], 4096, 512, 128);
    make_map(enc, &m.tm[1], d_in[2], 4096, 512, 128);
    make_map(enc, &m.tm[2], d_in[10], 512, 4096, 64);
    make_map(enc, &m.tm[3], d_in[5], 512, 4096, 64);
    make_map(enc, &m.tm[4], d_in[3], 4096, 512, 128);
    make_map(enc, &m.tm[5], d_in[4], 4096, 512, 128);
    make_map(enc, &m.tm[6], d_in[1], 512, 4 * 4096, 32);
    make_map(enc, &m.tm[7], d_in[8], 128, 128 * 4096, TK);
    p.xA = (const __nv_bfloat16*)d_in[0];
    p.xB = (const __nv_bfloat16*)d_in[6];
    p.K = (const __nv_bfloat16*)d_in[7];
    p.V = (const __nv_bfloat16*)d_in[8];
    p.out = (__nv_bfloat16*)d_out;
    cudaGetSymbolAddress((void**)&p.sc, g_scratch);
    fused_decode_kernel<<<NCTA, NTHREADS, SMEM_BYTES>>>(p, m);
}
```

```cpp
#include <cuda.h>
#include <cuda_runtime.h>
#include <cuda_bf16.h>
#include <stdint.h>

namespace {

#define TV_WSTART 3
#define TV_WMIN0 3
#define TV_WMIN 2
#define TV_IMIN 124
#define TV_LEAD 16
#define TV_LEADE 14
#define TV_WMAXE 3
#define TV_IEND 132
#define TV_TAU 640
#define TV_GAIN 1
#define TV_JUMP 400
#define TV_STAG 80
#define TV_QSLEEP 1600
#define TV_GSLEEP 3000
#define TV_ASLEEP 8
#define TV_ITE 6
#define TV_WESTEP 1
#define TV_CNT0 60
#define TV_MERGE 1
#define TV_MERGE0 6
#define TV_SVC 64
#define TV_GO 2
#define TV_TRIG 573
enum { T_WSTART, T_WMIN0, T_WMIN, T_IMIN, T_LEAD, T_LEADE, T_WMAXE, T_IEND, T_TAU, T_GAIN, T_JUMP, T_STAG, T_QSLEEP, T_GSLEEP, T_ASLEEP, T_ITE, T_WESTEP, T_CNT0, T_MERGE, T_MERGE0, T_SVC, T_GO, T_TRIG, T_COUNT };
#define TUNED(k) (TV_##k)

constexpr int TK = 64;
constexpr int TILE_BYTES = TK * 256;
constexpr int NS = 6;
constexpr int WMAX = 6;
constexpr int NSW = 8;
constexpr int NTHREADS = (4 + NSW) * 32;
constexpr int SPLIT = 4;
constexpr int AKEYS = 4096 / SPLIT;
constexpr int ATILES = AKEYS / 32;
constexpr int ASTAGES = 6;
constexpr int NCTA = 128;
constexpr int APER = 8;
constexpr int NB = NCTA - 4 * SPLIT;
constexpr int R_JOIN = 16, R_LATE = 17, N_EARLY = 120;
static_assert(R_JOIN * NB + (R_LATE - R_JOIN) * NCTA == N_EARLY * 16, "early chunks");
constexpr int I_LAST = 8 * R_LATE + 4;
constexpr int I_BOX = I_LAST + 4;
static_assert(I_LAST % NS + 4 <= NS && (I_LAST - 8 * R_JOIN) % NS + 4 <= NS, "the last V tiles share a lap");
__device__ __forceinline__ int late_pair(int vid) { return N_EARLY + (vid >> 4); }
__device__ __forceinline__ int chunk_of(int r, int vid) { return r * NB + max(r - R_JOIN, 0) * (NCTA - NB) + vid; }
__host__ __device__ constexpr int tiles4(int q) { return NB * q + (q > 32 * R_JOIN ? (NCTA - NB) * (q - 32 * R_JOIN) : 0); }

#define CGRP 16
constexpr int CHUNK_STEP = CGRP * TILE_BYTES;
__device__ __forceinline__ size_t chunk_off(unsigned c) { return (size_t)(4 * c - 3 * (c % CGRP)) * TILE_BYTES; }

constexpr int OFF_RING = 0;
constexpr int OFF_SIDE = NS * TILE_BYTES;
constexpr int OFF_SCR = OFF_SIDE + 98304;
constexpr int OFF_X = OFF_SCR;
constexpr int XROW = 264;
constexpr int OFF_RED = OFF_SCR + 8192;
constexpr int OFF_ARED = OFF_SCR;
constexpr int OFF_AP = OFF_ARED + 4 * 32 * 40 * 4;
constexpr int OFF_AALPHA = OFF_AP + 2 * 32 * 80;
constexpr int OFF_OPART = OFF_AALPHA + 256;
constexpr int OFF_ML = OFF_OPART + 2 * 512;
constexpr int OFF_PH = OFF_ML + 16;
constexpr int OFF_MLO = OFF_PH + 512;
constexpr int OFF_DONE = OFF_MLO + 32;
constexpr int OFF_WIN = OFF_DONE + 8;
constexpr int OFF_VEC = OFF_WIN + 8;
constexpr int OFF_Q = OFF_VEC + 4 * 68 * 4;
constexpr int OFF_BAR = OFF_Q + (R_LATE + 1) * 256;
enum { SI_WQ = 0, SI_WUK = 4, SI_WE = 6, SI_OPART = 10, SI_WO = 12, SI_COUNT = SI_WO + 5 };
enum {
    MB_X = 0, MB_SIDE = 1, MB_EARLY = MB_SIDE + 4,
    MB_FULL = MB_SIDE + SI_COUNT,
    MB_AFULL = MB_FULL + NS,
    MB_CNT = MB_AFULL + ASTAGES,
    MB_PH,
    MB_EMPTY,
    MB_F0 = MB_EMPTY + NS, MB_FU, MB_F2, MB_F3,
    MB_Q,
    MB_COUNT
};
constexpr int SMEM_BYTES = OFF_BAR + MB_COUNT * 8;
static_assert(SMEM_BYTES <= 232448, "smem");
constexpr int BLK_W = OFF_SIDE;
constexpr int BLK_U = OFF_SIDE + 65536;

constexpr int BAR_B = 9  , BAR_S = 2, BAR_R = 5, BAR_P = 6, BAR_E = 7;

constexpr float SCALE = 0.08838834764831845f;
constexpr float LOG2E = 1.4426950408889634f;
constexpr unsigned SPIN_LIMIT = 1u << 22;

struct Scratch {
    float opart[32 * SPLIT * 2048];
    unsigned qB[4 * 2048];
    unsigned qA[4 * 2048];
    unsigned qabs[4 * 8192];
    unsigned ctx[4 * 2048];
    unsigned oB[4 * 2048];
    unsigned part[2048 * 128];
    unsigned pml[2048 * 2];
    float2 ml[32 * SPLIT * 4];
    unsigned prog, pad[31];
    unsigned cnt;
};
__device__ __align__(128) Scratch g_scratch;

struct Ptrs {
    const __nv_bfloat16 *K, *V, *xA, *xB;
    __nv_bfloat16* out;
    Scratch* sc;
};
struct Maps {
    CUtensorMap tm[8];
};
struct Params : Ptrs {
    const CUtensorMap* tm;
};

#define PROF(i)
#define PROF2(i)

__device__ __forceinline__ uint32_t smem_u32(const void* p) { return (uint32_t)__cvta_generic_to_shared(p); }
__device__ __forceinline__ void mbar_init(uint32_t bar, int cnt) {
    asm volatile("mbarrier.init.shared::cta.b64 [%0], %1;" ::"r"(bar), "r"(cnt) : "memory");
}
__device__ __forceinline__ void mbar_expect_tx(uint32_t bar, uint32_t bytes) {
    asm volatile("mbarrier.arrive.expect_tx.shared::cta.b64 _, [%0], %1;" ::"r"(bar), "r"(bytes) : "memory");
}
__device__ __forceinline__ bool mbar_try(uint32_t bar, uint32_t parity) {
    uint32_t ok;
    asm volatile("{\n .reg .pred p;\n mbarrier.try_wait.parity.shared::cta.b64 p, [%1], %2;\n selp.u32 %0, 1, 0, p;\n}"
                 : "=r"(ok) : "r"(bar), "r"(parity) : "memory");
    return ok;
}
__device__ __forceinline__ void mbar_wait(uint32_t bar, uint32_t parity) {
    unsigned spins = 0;
    while (!mbar_try(bar, parity))
        if (++spins > SPIN_LIMIT) __trap();
}
__device__ __forceinline__ void mbar_wait_unless(bool done, uint32_t bar) {
    for (unsigned spins = 0; !done; done = mbar_try(bar, 0))
        if (++spins > SPIN_LIMIT) __trap();
}
__device__ __forceinline__ bool mbar_test(uint32_t bar, uint32_t parity) {
    uint32_t ok;
    asm volatile("{\n .reg .pred p;\n mbarrier.test_wait.parity.shared::cta.b64 p, [%1], %2;\n selp.u32 %0, 1, 0, p;\n}"
                 : "=r"(ok) : "r"(bar), "r"(parity) : "memory");
    return ok;
}
__device__ __forceinline__ void warp_release(uint32_t bar, int lane, float dep) {
    const uint32_t any = __ballot_sync(0xffffffffu, dep != dep);
    if (lane == 0)
        asm volatile("{\n .reg .pred q;\n setp.eq.u32 q, %1, 0;\n @q mbarrier.arrive.shared::cta.b64 _, [%0];\n"
                     " @!q mbarrier.arrive.shared::cta.b64 _, [%0];\n}" ::"r"(bar), "r"(any) : "memory");
}
__device__ __forceinline__ bool elect_one() {
    uint32_t e;
    asm volatile("{\n .reg .pred p;\n elect.sync _|p, 0xffffffff;\n selp.u32 %0, 1, 0, p;\n}" : "=r"(e));
    return e;
}
__device__ __forceinline__ int lds_volatile(uint32_t addr) {
    int v;
    asm volatile("ld.volatile.shared.u32 %0, [%1];" : "=r"(v) : "r"(addr) : "memory");
    return v;
}
__device__ __forceinline__ int2 lds_volatile2(uint32_t addr) {
    int2 v;
    asm volatile("ld.volatile.shared.v2.u32 {%0, %1}, [%2];" : "=r"(v.x), "=r"(v.y) : "r"(addr) : "memory");
    return v;
}
__device__ __forceinline__ void sts_volatile2(uint32_t addr, int a, int b) {
    asm volatile("st.volatile.shared.v2.u32 [%0], {%1, %2};" ::"r"(addr), "r"(a), "r"(b) : "memory");
}
__device__ __forceinline__ void sts_volatile(uint32_t addr, int v) {
    asm volatile("st.volatile.shared.u32 [%0], %1;" ::"r"(addr), "r"(v) : "memory");
}
__device__ __forceinline__ unsigned now_ns() {
    unsigned t;
    asm volatile("mov.u32 %0, %%globaltimer_lo;" : "=r"(t) :: "memory");
    return t;
}
__device__ __forceinline__ int clock_after(unsigned dep) {
    int c;
    asm volatile("{\n .reg .pred q;\n setp.eq.u32 q, %1, 0;\n @q mov.u32 %0, %%globaltimer_lo;\n @!q mov.u32 %0, %%globaltimer_lo;\n}" : "=r"(c) : "r"(dep) : "memory");
    return c;
}
__device__ __forceinline__ void fence_mbar_init() { asm volatile("fence.mbarrier_init.release.cluster;" ::: "memory"); }
__device__ __forceinline__ uint64_t policy_evict_first() {
    uint64_t pol;
    asm volatile("createpolicy.fractional.L2::evict_first.b64 %0, 1.0;" : "=l"(pol));
    return pol;
}
__device__ __forceinline__ uint64_t policy_evict_normal() {
    uint64_t pol;
    asm volatile("createpolicy.fractional.L2::evict_normal.b64 %0, 1.0;" : "=l"(pol));
    return pol;
}
__device__ __forceinline__ void bulk_load(uint32_t dst, const void* src, uint32_t bytes, uint32_t bar, uint64_t pol) {
    asm volatile("cp.async.bulk.shared::cluster.global.mbarrier::complete_tx::bytes.L2::cache_hint [%0], [%1], %2, [%3], %4;"
                 ::"r"(dst), "l"(src), "r"(bytes), "r"(bar), "l"(pol) : "memory");
}
__device__ __forceinline__ void bulk_load_nohint(uint32_t dst, const void* src, uint32_t bytes, uint32_t bar) {
    asm volatile("cp.async.bulk.shared::cluster.global.mbarrier::complete_tx::bytes [%0], [%1], %2, [%3];"
                 ::"r"(dst), "l"(src), "r"(bytes), "r"(bar) : "memory");
}
__device__ __forceinline__ void tma2d_hint(uint32_t dst, const CUtensorMap* tm, int x, int y, uint32_t bar, uint64_t pol) {
    asm volatile("cp.async.bulk.tensor.2d.shared::cluster.global.mbarrier::complete_tx::bytes.L2::cache_hint [%0], [%1, {%3, %4}], [%2], %5;"
                 ::"r"(dst), "l"(tm), "r"(bar), "r"(x), "r"(y), "l"(pol) : "memory");
}
__device__ __forceinline__ void ldsm4(uint32_t& r0, uint32_t& r1, uint32_t& r2, uint32_t& r3, uint32_t addr) {
    asm volatile("ldmatrix.sync.aligned.m8n8.x4.shared.b16 {%0,%1,%2,%3}, [%4];"
                 : "=r"(r0), "=r"(r1), "=r"(r2), "=r"(r3) : "r"(addr) : "memory");
}
__device__ __forceinline__ void ldsm4t(uint32_t& r0, uint32_t& r1, uint32_t& r2, uint32_t& r3, uint32_t addr) {
    asm volatile("ldmatrix.sync.aligned.m8n8.x4.trans.shared.b16 {%0,%1,%2,%3}, [%4];"
                 : "=r"(r0), "=r"(r1), "=r"(r2), "=r"(r3) : "r"(addr) : "memory");
}
__device__ __forceinline__ void mma(float (&c)[4], uint32_t a0, uint32_t a1, uint32_t a2, uint32_t a3, uint32_t b0, uint32_t b1) {
    asm volatile("mma.sync.aligned.m16n8k16.row.col.f32.bf16.bf16.f32 {%0,%1,%2,%3}, {%4,%5,%6,%7}, {%8,%9}, {%0,%1,%2,%3};"
                 : "+f"(c[0]), "+f"(c[1]), "+f"(c[2]), "+f"(c[3])
                 : "r"(a0), "r"(a1), "r"(a2), "r"(a3), "r"(b0), "r"(b1));
}
__device__ __forceinline__ void zero4(float (&c)[4]) { c[0] = c[1] = c[2] = c[3] = 0.f; }
__device__ __forceinline__ void bar_sync(int id, int n) { asm volatile("bar.sync %0, %1;" ::"r"(id), "r"(n) : "memory"); }
__device__ __forceinline__ void bar_arrive(int id, int n) { asm volatile("bar.arrive %0, %1;" ::"r"(id), "r"(n) : "memory"); }
__device__ __forceinline__ float ex2(float x) { float y; asm("ex2.approx.ftz.f32 %0, %1;" : "=f"(y) : "f"(x)); return y; }
__device__ __forceinline__ uint32_t pack_bf16(float lo, float hi) {
    uint32_t r; asm("cvt.rn.bf16x2.f32 %0, %1, %2;" : "=r"(r) : "f"(hi), "f"(lo)); return r;
}
__device__ __forceinline__ float bf_lo(uint32_t u) { return __uint_as_float(u << 16); }
__device__ __forceinline__ float bf_hi(uint32_t u) { return __uint_as_float(u & 0xffff0000u); }
__device__ __forceinline__ uint32_t score_round2(float a, float b) {
    const uint32_t u = pack_bf16(a, b);
    return pack_bf16(bf_lo(u) * SCALE, bf_hi(u) * SCALE);
}
__device__ __forceinline__ float warp_max(float v) {
#pragma unroll
    for (int o = 16; o > 0; o >>= 1) v = fmaxf(v, __shfl_xor_sync(0xffffffffu, v, o));
    return v;
}
__device__ __forceinline__ float redux_max(float v) {
    const int i = __float_as_int(v), m = __reduce_max_sync(0xffffffffu, i ^ ((i >> 31) & 0x7fffffff));
    return __int_as_float(m ^ ((m >> 31) & 0x7fffffff));
}
__device__ __forceinline__ float warp_sum(float v) {
#pragma unroll
    for (int o = 16; o > 0; o >>= 1) v += __shfl_xor_sync(0xffffffffu, v, o);
    return v;
}

__device__ __forceinline__ void ll_store(unsigned* p, unsigned bits) {
    unsigned u = ~bits;
    u = u ? u : 0x80008000u;
    asm volatile("st.relaxed.gpu.global.u32 [%0], %1;" ::"l"(p), "r"(u) : "memory");
}
__device__ __forceinline__ void ll_store2(unsigned* p, unsigned a, unsigned b) {
    unsigned u = ~a, v = ~b;
    u = u ? u : 0x80008000u;
    v = v ? v : 0x80008000u;
    asm volatile("st.relaxed.gpu.global.v2.u32 [%0], {%1, %2};" ::"l"(p), "r"(u), "r"(v) : "memory");
}
__device__ __forceinline__ void ll_store4(unsigned* p, float a, float b, float c, float d) {
    unsigned u[4] = {~__float_as_uint(a), ~__float_as_uint(b), ~__float_as_uint(c), ~__float_as_uint(d)};
#pragma unroll
    for (int k = 0; k < 4; k++) u[k] = u[k] ? u[k] : 0x80008000u;
    asm volatile("st.relaxed.gpu.global.v4.u32 [%0], {%1, %2, %3, %4};" ::"l"(p), "r"(u[0]), "r"(u[1]), "r"(u[2]), "r"(u[3]) : "memory");
}
__device__ __forceinline__ unsigned ll_load(const unsigned* p) {
    unsigned u;
    asm volatile("ld.relaxed.gpu.global.u32 %0, [%1];" : "=r"(u) : "l"(p) : "memory");
    return u;
}
__device__ __forceinline__ uint2 ll_load2(const unsigned* p) {
    uint2 v;
    asm volatile("ld.relaxed.gpu.global.v2.u32 {%0,%1}, [%2];" : "=r"(v.x), "=r"(v.y) : "l"(p) : "memory");
    return v;
}
__device__ __forceinline__ uint4 ll_load4(const unsigned* p) {
    uint4 v;
    asm volatile("ld.relaxed.gpu.global.v4.u32 {%0,%1,%2,%3}, [%4];" : "=r"(v.x), "=r"(v.y), "=r"(v.z), "=r"(v.w) : "l"(p) : "memory");
    return v;
}
__device__ __forceinline__ bool ll_ok4(const uint4& v) { return min(min(v.x, v.y), min(v.z, v.w)) != 0u; }
template <int N>
__device__ __forceinline__ void ll_poll4(uint4 (&v)[N], const unsigned* p, int stride, unsigned sleep_ns = 0) {
    unsigned spins = 0;
    while (true) {
        bool ok = true;
#pragma unroll
        for (int k = 0; k < N; k++) v[k] = ll_load4(p + k * stride);
#pragma unroll
        for (int k = 0; k < N; k++) ok = ok && ll_ok4(v[k]);
        if (ok) break;
        if (sleep_ns) __nanosleep(sleep_ns);
        if (++spins > SPIN_LIMIT) __trap();
    }
    __syncwarp();
#pragma unroll
    for (int k = 0; k < N; k++) v[k] = make_uint4(~v[k].x, ~v[k].y, ~v[k].z, ~v[k].w);
}

__device__ __forceinline__ void bump_counter(unsigned* c) {
    asm volatile("red.relaxed.gpu.global.inc.u32 [%0], %1;" ::"l"(c), "r"(4 * SPLIT + 128 - 1) : "memory");
}
__device__ __forceinline__ void signal_counter(unsigned* c) {
    asm volatile("fence.acq_rel.gpu;" ::: "memory");
    bump_counter(c);
}
__device__ __forceinline__ unsigned ld_acquire(const unsigned* c) {
    unsigned v;
    asm volatile("ld.acquire.gpu.global.u32 %0, [%1];" : "=r"(v) : "l"(c) : "memory");
    return v;
}
__device__ __forceinline__ uint32_t pv_mask(int c, int g, int t) {
    return (c == (g ^ (2 * t)) ? 0x0000ffffu : 0u) | (c == (g ^ (2 * t + 1)) ? 0xffff0000u : 0u);
}

struct Producer {
    uint32_t sbase;
    uint32_t wbar, wpar;
    bool pend;
    int lane;
    uint64_t pol;
    uint32_t si_dst, si_gate;
    int si_x, si_y, si_min;
    bool si_box;
    const void* si_src;
    uint64_t si_pol;
    __device__ __forceinline__ uint32_t mb(int i) const { return sbase + OFF_BAR + i * 8; }
    __device__ __forceinline__ void setup_side(const Params& p, int vid) {
        const int cbk = vid >> 1, u = lane & 1;
        si_box = true; si_min = 0; si_gate = mb(MB_X);
        si_pol = lane >= SI_OPART ? policy_evict_normal() : pol;
        int blk = BLK_U + u * 16384;
        if (lane >= SI_OPART) {
            si_box = false; si_src = p.sc->opart + ((cbk >> 1) * SPLIT + 2 * u) * 2048;
            si_gate = mb(MB_CNT);
        } else if (lane >= SI_WE) {
            const int q = lane - SI_WE;
            si_src = &p.tm[5]; blk = BLK_W + q * 16384;
            si_x = 64 * cbk; si_y = 128 * q;
            si_gate = mb(MB_F0); si_min = TUNED(ITE) + TUNED(WESTEP) * q;
        } else {
            si_src = &p.tm[4]; si_x = (vid & 31) * 128 + 64 * u; si_y = 128 * (vid >> 5);
        }
        si_dst = sbase + blk;
    }
    __device__ __forceinline__ bool due(const Params& p, int i, int2 st) const {
        return st.y && (int)(now_ns() - st.y) >= tiles4(4 * i - (i < TUNED(IEND) ? TUNED(LEAD) : TUNED(LEADE))) * TUNED(TAU) / 512;
    }
    __device__ __forceinline__ void window(const Params& p, int i, uint32_t bar, uint32_t parity) {
        unsigned busy;
        for (unsigned spins = 0;; spins++) {
            const int2 st = lds_volatile2(sbase + OFF_WIN);
            if (pend) pend = !mbar_test(wbar, wpar);
            busy = __ballot_sync(0xffffffffu, pend);
            const int n = __popc(busy);
            if (__any_sync(0xffffffffu, n < st.x || (n < (i < TUNED(IEND) ? WMAX : TUNED(WMAXE)) && due(p, i, st)))) break;
            if (spins > 16 * SPIN_LIMIT) __trap();
        }
        if (lane == __ffs(~busy) - 1) { wbar = bar; wpar = parity; pend = true; }
    }
    __device__ __forceinline__ void side(const Params& p, int id) {
        const uint32_t bar = mb(MB_SIDE + id);
        if (id < SI_OPART) window(p, 0, bar, 0);
        if (lane == id) {
            mbar_expect_tx(bar, TILE_BYTES);
            if (si_box) {
                tma2d_hint(si_dst, (const CUtensorMap*)si_src, si_x, si_y, bar, si_pol);
            } else {
                asm volatile("fence.proxy.async.global;" ::: "memory");
                bulk_load(si_dst, si_src, TILE_BYTES, bar, si_pol);
            }
        }
        __syncwarp();
    }
    __device__ __forceinline__ void a_tile(const Params& p, int row0, int n) {
        const int st = n % ASTAGES;
        if (lane == 0) mbar_expect_tx(mb(MB_AFULL + st), 32768);
        __syncwarp();
        if (lane < 8) tma2d_hint(sbase + st * 32768 + lane * 4096, &p.tm[6], lane * 64, row0 + n * (32 * SPLIT), mb(MB_AFULL + st), pol);
        __syncwarp();
    }
};

__device__ __forceinline__ void first_load(const Params& p, uint32_t sbase, unsigned blk) {
    const uint32_t bar = sbase + OFF_BAR + MB_FULL * 8;
    mbar_init(bar, 1);
    if (blk % APER != APER - 1) {
        const unsigned c = blk % APER * 16 + blk / APER;
        fence_mbar_init();
        mbar_expect_tx(bar, TILE_BYTES);
        bulk_load(sbase + OFF_RING, (const char*)p.K + chunk_off(c), TILE_BYTES, bar, policy_evict_first());
    }
}
__device__ __forceinline__ void next_loads(const Params& p, uint32_t sbase, int vid) {
    const uint32_t bars = sbase + OFF_BAR;
    const uint64_t pol = policy_evict_first();
#pragma unroll
    for (int i = 0; i < MB_EARLY; i++) mbar_init(bars + i * 8, 1);
    fence_mbar_init();
#pragma unroll
    for (int q = 0; q < 4; q++) {
        mbar_expect_tx(bars + (MB_SIDE + q) * 8, TILE_BYTES);
        tma2d_hint(sbase + BLK_W + q * 16384, &p.tm[vid & 1], 64 * (vid >> 1), 128 * q, bars + (MB_SIDE + q) * 8, pol);
        if (q == 0) {
            mbar_expect_tx(bars + MB_X * 8, 4096);
            bulk_load_nohint(sbase + OFF_X, (vid & 1) ? p.xA : p.xB, 4096, bars + MB_X * 8);
        }
    }
}

__device__ __forceinline__ void produce(const Params& p, char* smem, int lane, bool isA, int vid, int row0) {
    Producer pr;
    pr.sbase = smem_u32(smem);
    pr.lane = lane;
    pr.pol = policy_evict_first();
    pr.pend = !isA && lane < 5;
    pr.wbar = pr.mb(lane == 0 ? MB_FULL : MB_SIDE + lane - 1);
    pr.wpar = 0;
    pr.setup_side(p, vid);
    const int i0 = isA ? 8 * R_JOIN : 0;
    int i = isA ? i0 : 1, i_end = isA ? i0 : I_LAST, s = i - i0, ph = 0;
    int chunk = chunk_of(i >> 3, vid);
    const char* src = (const char*)p.K + chunk_off(chunk) + (i & 3) * CHUNK_STEP;
    int nx = SI_WUK, nx_end = isA || (vid & 1) ? SI_WE : SI_WO;
    uint32_t gate = pr.mb(MB_X);
    int gmin = 0;
    bool last_tile = false;
#pragma unroll 1
    for (int phase = 0; phase < 3; phase++) {
#pragma unroll 1
        while (i < i_end || nx < nx_end) {
            if (nx < nx_end && i >= gmin) {
                bool side = true;
                if (i == i_end) mbar_wait(gate, 0);
                else side = __all_sync(0xffffffffu, mbar_test(gate, 0) &&
                                       (last_tile || (i - i0 >= NS && !mbar_test(pr.mb(MB_EMPTY + s), ph ^ 1))));
                if (side) {
                    last_tile = false;
                    pr.side(p, nx);
                    PROF2(160 + nx);
                    nx++;
                    gate = __shfl_sync(0xffffffffu, pr.si_gate, nx);
                    gmin = __shfl_sync(0xffffffffu, pr.si_min, nx);
                    continue;
                }
            }
            last_tile = true;
            const uint32_t full = pr.mb(MB_FULL + s);
            mbar_wait(pr.mb(MB_EMPTY + s), ph ^ 1);
            if (elect_one()) mbar_expect_tx(full, TILE_BYTES);
            pr.window(p, i, full, ph);
            if (elect_one()) bulk_load(pr.sbase + OFF_RING + s * TILE_BYTES, src, TILE_BYTES, full, pr.pol);
            PROF2(i);
            src += CHUNK_STEP;
            if ((++i & 3) == 0) {
                if ((i & 4) == 0) chunk = chunk_of(i >> 3, vid);
                src = (const char*)((i & 4) ? p.V : p.K) + chunk_off(chunk);
            }
            if (++s == NS) { s = 0; ph ^= 1; }
        }
        if (!isA || phase == 2) break;
        if (phase == 0) {
#pragma unroll 1
            for (int k = -ASTAGES; k < ATILES; k++) {
                if (k == 3 - ASTAGES) mbar_wait(pr.mb(MB_FU), 0);
                if (k >= 0) bar_sync(BAR_R, 352);
                const int n = k < 0 ? k + ASTAGES : k - 2 + ASTAGES;
                if ((k < 0 || k >= 2) && n < ATILES) { pr.a_tile(p, row0, n); PROF2(32 + n); }
            }
            mbar_wait(pr.mb(MB_F3), 0);
            if (!(vid & 1)) nx_end = SI_WO;
        } else {
            for (int k = 0; k < 500 && !__any_sync(0xffffffffu, pr.due(p, i0, lds_volatile2(pr.sbase + OFF_WIN))); k++) __nanosleep(100);
            i_end = I_LAST;
        }
    }
#pragma unroll 1
    for (int u = 0; u < 4; u++) {
        const uint32_t full = pr.mb(MB_FULL + s + u);
        mbar_wait(pr.mb(MB_EMPTY + s + u), ph ^ 1);
        if (elect_one()) mbar_expect_tx(full, TILE_BYTES);
        pr.window(p, I_LAST + u, full, ph);
        if (elect_one()) {
#pragma unroll
            for (int hf = 0; hf < 2; hf++)
                tma2d_hint(pr.sbase + OFF_RING + (s + u) * TILE_BYTES + hf * 8192, &p.tm[7], 64 * hf,
                           (chunk_off(chunk) + u * CHUNK_STEP) / 256, full, pr.pol);
        }
        PROF2(I_LAST + u);
    }
    mbar_wait(pr.mb((vid & 1) ? MB_F0 : MB_F2), 0);
#pragma unroll 1
    for (int u = 0; u < 4; u++) {
        const uint32_t bar = pr.mb(MB_SIDE + SI_WO + u);
        if (elect_one()) {
            mbar_expect_tx(bar, u < 3 ? TILE_BYTES : TILE_BYTES / 2);
            if (u == 3) mbar_expect_tx(bar + 8, TILE_BYTES / 2);
        }
        pr.window(p, I_BOX + u, bar, 0);
        if (elect_one()) {
#pragma unroll
            for (int k = 0; k < 2; k++)
                tma2d_hint(pr.sbase + BLK_W + u * TILE_BYTES + k * (TILE_BYTES / 2), &p.tm[2 + (vid & 1)], 64 * ((vid >> 1) & 7),
                           1024 * u + 128 * (vid >> 4) + 64 * k, bar + (u == 3 ? 8 * k : 0), pr.pol);
        }
        PROF2(I_BOX + u);
    }
}

__device__ __forceinline__ void consume(const Params& p, char* smem, bool isA, int vid, int w, int lane) {
    const uint32_t sbase = smem_u32(smem);
    const uint32_t bars = sbase + OFF_BAR;
    const int g = lane >> 2, t = lane & 3;
    const int mat = lane >> 3, r8 = lane & 7;
    const uint32_t kbase = sbase + OFF_RING + (r8 + 8 * (mat & 1)) * 256 + (mat >> 1) * 128 + r8 * 16;
    const uint32_t vbase = sbase + OFF_RING + (r8 + 8 * (mat >> 1)) * 256 + (mat & 1) * 128 + r8 * 16;
    uint32_t mask[8];
#pragma unroll
    for (int c = 0; c < 8; c++) mask[c] = pv_mask(c, g, t);
    uint32_t* qtab = (uint32_t*)(smem + OFF_Q);
    if (!isA) {
        mbar_wait(bars + MB_F0 * 8, 0);
        __nanosleep(TUNED(QSLEEP));
        const unsigned* src = p.sc->qB + (chunk_of(0, vid) >> 4) * 64 + lane;
        unsigned q0, q1, spins = 0;
        while (true) {
            q0 = ll_load(src);
            q1 = ll_load(src + 32);
            if (q0 && q1) break;
            __nanosleep(200);
            if (++spins > SPIN_LIMIT) __trap();
        }
        qtab[lane] = ~q0;
        qtab[32 + lane] = ~q1;
        __syncwarp();
        if (w == 0) PROF(1);
    }
    int s = w, ph = 0;
    int done = 0;
#pragma unroll 1
    for (int r = isA ? R_JOIN : 0;; r++) {
        const int chunk = chunk_of(r, vid);
        if (r >= 1) mbar_wait(bars + MB_Q * 8, 0);
        uint32_t qf[8][2];
#pragma unroll
        for (int c = 0; c < 8; c++) {
            qf[c][0] = qtab[r * 64 + (c ^ g) * 4 + t];
            qf[c][1] = qtab[r * 64 + 32 + (c ^ g) * 4 + t];
        }
        uint32_t pf[2][4][2];
        float m[2], l[2];
#pragma unroll
        for (int u = 0; u < 2; u++) {
            mbar_wait(bars + (MB_FULL + s) * 8, ph);
            done++;
            float acc[4][4];
#pragma unroll
            for (int gr = 0; gr < 4; gr++) zero4(acc[gr]);
#pragma unroll
            for (int c = 0; c < 8; c++) {
#pragma unroll
                for (int gr = 0; gr < 4; gr++) {
                    uint32_t a0, a1, a2, a3;
                    ldsm4(a0, a1, a2, a3, (kbase ^ (c << 4)) + s * TILE_BYTES + gr * 4096);
                    mma(acc[gr], a0, a1, a2, a3, qf[c][0], qf[c][1]);
                }
            }
            warp_release(bars + (MB_EMPTY + s) * 8, lane, (acc[0][0] + acc[1][0]) + (acc[2][0] + acc[3][0]));
#pragma unroll
            for (int gr = 0; gr < 4; gr++) {
                const uint32_t su = score_round2((g & 1) ? acc[gr][1] : acc[gr][0], (g & 1) ? acc[gr][3] : acc[gr][2]);
                const uint32_t x = __shfl_sync(0xffffffffu, su, 9 * t), y = __shfl_sync(0xffffffffu, su, 9 * t + 4);
                pf[u][gr][0] = __byte_perm(x, y, 0x5410);
                pf[u][gr][1] = __byte_perm(x, y, 0x7632);
            }
            m[u] = -INFINITY;
            l[u] = 0.f;
#pragma unroll
            for (int k = 0; k < 8; k++) m[u] = fmaxf(m[u], fmaxf(bf_lo(pf[u][k >> 1][k & 1]), bf_hi(pf[u][k >> 1][k & 1])));
            m[u] = fmaxf(m[u], __shfl_xor_sync(0xffffffffu, m[u], 1));
            m[u] = fmaxf(m[u], __shfl_xor_sync(0xffffffffu, m[u], 2));
#pragma unroll
            for (int k = 0; k < 8; k++) {
                uint32_t& x = pf[u][k >> 1][k & 1];
                const float e0 = ex2((bf_lo(x) - m[u]) * LOG2E), e1 = ex2((bf_hi(x) - m[u]) * LOG2E);
                l[u] += e0 + e1;
                x = pack_bf16(e0, e1);
            }
            l[u] += __shfl_xor_sync(0xffffffffu, l[u], 1);
            l[u] += __shfl_xor_sync(0xffffffffu, l[u], 2);
            if (lane == 0) sts_volatile(sbase + OFF_DONE + 4 * w, done);
            if (r == R_LATE) {
                if (lane < 4) {
                    uint4* dst = (uint4*)(smem + OFF_PH + (2 * u + w) * 128 + t * 32);
                    dst[0] = make_uint4(pf[u][0][0], pf[u][0][1], pf[u][1][0], pf[u][1][1]);
                    dst[1] = make_uint4(pf[u][2][0], pf[u][2][1], pf[u][3][0], pf[u][3][1]);
                    if (lane == 0) ((float2*)(smem + OFF_MLO))[2 * u + w] = make_float2(m[u], l[u]);
                }
                __syncwarp();
                if (lane == 0) mbar_expect_tx(bars + MB_PH * 8, 0);
            }
            if ((s += 2) >= NS) { s -= NS; ph ^= 1; }
        }
        if (r == R_LATE) break;
        const float mw = fmaxf(m[0], m[1]);
        float o[4] = {0.f, 0.f, 0.f, 0.f}, lw = 0.f;
#pragma unroll
        for (int u = 0; u < 2; u++) {
            const float a = ex2((m[u] - mw) * LOG2E);
            lw = fmaf(a, l[u], lw);
            float oacc[4][4];
#pragma unroll
            for (int gr = 0; gr < 4; gr++) zero4(oacc[gr]);
            mbar_wait(bars + (MB_FULL + s) * 8, ph);
            PROF(u ? 2 + w : 19 + w);
            done++;
#pragma unroll
            for (int c = 0; c < 8; c++) {
#pragma unroll
                for (int gr = 0; gr < 4; gr++) {
                    uint32_t a0, a1, a2, a3;
                    ldsm4t(a0, a1, a2, a3, (vbase ^ (c << 4)) + s * TILE_BYTES + gr * 4096);
                    mma(oacc[gr], a0, a1, a2, a3, pf[u][gr][0] & mask[c], pf[u][gr][1] & mask[c]);
                }
            }
#pragma unroll
            for (int e = 0; e < 4; e++) o[e] = fmaf(a, (oacc[0][e] + oacc[1][e]) + (oacc[2][e] + oacc[3][e]), o[e]);
            warp_release(bars + (MB_EMPTY + s) * 8, lane, o[0]);
            if (lane == 0) sts_volatile(sbase + OFF_DONE + 4 * w, done);
            if ((s += 2) >= NS) { s -= NS; ph ^= 1; }
        }
        float4* op = (float4*)(smem + OFF_OPART) + (r & 1) * 32 + lane;
        float2* ml = (float2*)(smem + OFF_ML) + (r & 1);
        if (w == 0) {
            *op = make_float4(o[0], o[1], o[2], o[3]);
            if (lane == 0) *ml = make_float2(mw, lw);
            bar_arrive(BAR_B + (r & 1), 64);
        } else {
            bar_sync(BAR_B + (r & 1), 64);
            const float2 ot = *ml;
            const float4 oo = *op;
            const float M = fmaxf(mw, ot.x), a = ex2((mw - M) * LOG2E), b = ex2((ot.x - M) * LOG2E);
            ll_store4(p.sc->part + chunk * 128 + lane * 4, a * o[0] + b * oo.x, a * o[1] + b * oo.y,
                      a * o[2] + b * oo.z, a * o[3] + b * oo.w);
            if (lane == 0) ll_store2(p.sc->pml + chunk * 2, __float_as_uint(M), __float_as_uint(a * lw + b * ot.y));
            PROF(10);
        }
    }
}

__device__ __forceinline__ uint2 merge_chunks(const Params& p, int pair, int lane) {
    Scratch* sc = p.sc;
    const unsigned* pm = sc->pml + pair * 32 + 2 * (lane & 15);
    const unsigned* base = sc->part + pair * 2048 + 4 * lane;
    unsigned um = 0, ul = 0;
    uint4 u[16];
#pragma unroll
    for (int c = 0; c < 16; c++) u[c] = make_uint4(0, 0, 0, 0);
    for (unsigned spins = 0;; spins++) {
        if (!(um && ul)) { um = ll_load(pm); ul = ll_load(pm + 1); }
#pragma unroll
        for (int c = 0; c < 16; c++)
            if (!ll_ok4(u[c])) u[c] = ll_load4(base + c * 128);
        bool ok = um && ul;
#pragma unroll
        for (int c = 0; c < 16; c++) ok &= ll_ok4(u[c]);
        if (__all_sync(0xffffffffu, ok)) break;
        __nanosleep(100);
        if (spins > SPIN_LIMIT) __trap();
    }
    const float m = __uint_as_float(~um);
    const float M = redux_max(m);
    const float wgt = ex2((m - M) * LOG2E);
    float l = wgt * __uint_as_float(~ul);
#pragma unroll
    for (int k = 8; k > 0; k >>= 1) l += __shfl_xor_sync(0xffffffffu, l, k);
    float o[4] = {0.f, 0.f, 0.f, 0.f};
#pragma unroll
    for (int c = 0; c < 16; c++) {
        const float wc = __shfl_sync(0xffffffffu, wgt, c);
        o[0] = fmaf(wc, __uint_as_float(~u[c].x), o[0]); o[1] = fmaf(wc, __uint_as_float(~u[c].y), o[1]);
        o[2] = fmaf(wc, __uint_as_float(~u[c].z), o[2]); o[3] = fmaf(wc, __uint_as_float(~u[c].w), o[3]);
    }
    const float inv = __frcp_rn(l);
    const uint32_t lo = pack_bf16(o[0] * inv, o[2] * inv), hi = pack_bf16(o[1] * inv, o[3] * inv);
    const bool odd = lane & 4;
    const uint32_t x = __shfl_xor_sync(0xffffffffu, odd ? lo : hi, 4), a = odd ? x : lo, b = odd ? hi : x;
    return make_uint2(__byte_perm(a, b, 0x5410), __byte_perm(a, b, 0x7632));
}

__device__ __forceinline__ int qabs_word(int b, int h, int j, int ks, int nt, int t) {
    return b * 8192 + (((h >> 4) + 2 * j) * 8 + ks) * 128 + ((h & 7) * 4 + t) * 4 + ((h >> 3) & 1) + 2 * nt;
}
__device__ __forceinline__ void service(const Params& p, char* smem, bool isA, int vid, int lane) {
    const uint32_t sbase = smem_u32(smem);
    const int i0 = isA ? 8 * R_JOIN : 0;
    const int c = 16 * vid + 15;
    const int rl = c < R_JOIN * NB ? c / NB : R_JOIN + (c - R_JOIN * NB) / NCTA;
    const int due = 8 * (rl + 1) + (rl + 1 == R_LATE ? TUNED(MERGE) : TUNED(MERGE0));
    const int ow = 8 * (lane & 3) + (lane & 4) + (lane >> 3);
    bool merged = vid >= N_EARLY, counted = false;
    int last = i0, z = 0;
    unsigned t0 = clock(), t1 = t0, prev = 0;
    if (isA) mbar_wait(sbase + OFF_BAR + MB_F3 * 8, 0);
    for (unsigned spins = 0; last < I_BOX || !counted || !merged; spins++) {
        const int pos = __shfl_sync(0xffffffffu, i0 + lds_volatile(sbase + OFF_DONE) + lds_volatile(sbase + OFF_DONE + 4), 0);
        if (!merged && pos > due) {
            const int pair = vid;
            const uint2 o = merge_chunks(p, pair, lane);
            ll_store(p.sc->oB + pair * 64 + ow, o.x);
            ll_store(p.sc->oB + pair * 64 + ow + 32, o.y);
#pragma unroll
            for (int k = 0; k < 16; k++) *(uint4*)(p.sc->part + pair * 2048 + k * 128 + 4 * lane) = make_uint4(0, 0, 0, 0);
            p.sc->pml[pair * 32 + lane] = 0;
            *(uint2*)(p.sc->qB + pair * 64 + 2 * lane) = make_uint2(0, 0);
            PROF(12);
            merged = true;
            continue;
        }
        const unsigned now = __shfl_sync(0xffffffffu, (unsigned)clock(), 0);
        const bool look = pos > last || (isA && pos == i0 && now - t1 > 2000);
        unsigned old = 0;
        if (look && lane == 0) old = pos > last ? atomicAdd(&p.sc->prog, pos - last) : ll_load(&p.sc->prog);
        if (!counted && now - t0 > 2000 && (isA || pos > TUNED(CNT0))) {
            t0 = now;
            if (__all_sync(0xffffffffu, ld_acquire(&p.sc->cnt) >= 4 * SPLIT)) {
                if (lane == 0) {
                    mbar_expect_tx(sbase + OFF_BAR + MB_CNT * 8, 0);
                    bump_counter(&p.sc->cnt);
                }
                *(uint2*)(p.sc->qA + vid * 64 + lane * 2) = make_uint2(0, 0);
                *(uint4*)(p.sc->qabs + vid * 256 + lane * 4) = make_uint4(0, 0, 0, 0);
                *(uint4*)(p.sc->qabs + vid * 256 + 128 + lane * 4) = make_uint4(0, 0, 0, 0);
                counted = true;
            }
        }
        if (look) {
            if (lane == 0) {
                if (pos > last && old + (pos - last) == tiles4(4 * I_BOX) / 4) p.sc->prog = 0;
                if (old > prev && old >= 6 * NB && old < tiles4(4 * I_BOX - 8) / 4) {
                    const int zn = clock_after(old) - old * TUNED(TAU) / 128 + (vid >> 4) * TUNED(STAG);
                    z = prev && zn - z < TUNED(JUMP) ? z + ((zn - z) >> TUNED(GAIN)) : zn;
                    prev = old;
                    sts_volatile2(sbase + OFF_WIN, 4 * old < tiles4(4 * TUNED(IMIN)) ? TUNED(WMIN0) : TUNED(WMIN), z);
                }
            }
            t1 = now;
        } else {
            __nanosleep(TUNED(SVC));
        }
        last = pos;
        if (spins > SPIN_LIMIT) __trap();
    }
}

__device__ __forceinline__ void softmax_A(const Params& p, char* smem, int w, int lane, int ab, int asp) {
    const int mat = lane >> 3, r = lane & 7;
    float m_run[4], l_run[4];
#pragma unroll
    for (int i = 0; i < 4; i++) { m_run[i] = -INFINITY; l_run[i] = 0.f; }
    const float* red = (const float*)(smem + OFF_ARED);
    for (int k = 0; k < ATILES; k++) {
        bar_sync(BAR_R, 352);
        float4 s[4];
        float mt[4];
#pragma unroll
        for (int i = 0; i < 4; i++) {
            const float* src = red + (16 * w + 4 * i + mat) * 40 + 4 * r;
            const float4 a = *(const float4*)src, b = *(const float4*)(src + 32 * 40);
            const float4 c = *(const float4*)(src + 64 * 40), d = *(const float4*)(src + 96 * 40);
            const uint32_t v0 = score_round2((a.x + b.x) + (c.x + d.x), (a.y + b.y) + (c.y + d.y));
            const uint32_t v1 = score_round2((a.z + b.z) + (c.z + d.z), (a.w + b.w) + (c.w + d.w));
            s[i] = make_float4(bf_lo(v0), bf_hi(v0), bf_lo(v1), bf_hi(v1));
            mt[i] = fmaxf(fmaxf(s[i].x, s[i].y), fmaxf(s[i].z, s[i].w));
        }
#pragma unroll
        for (int o = 1; o < 8; o <<= 1)
#pragma unroll
            for (int i = 0; i < 4; i++) mt[i] = fmaxf(mt[i], __shfl_xor_sync(0xffffffffu, mt[i], o));
#pragma unroll
        for (int i = 0; i < 4; i++) {
            const int head = 16 * w + 4 * i + mat;
            const float m_new = fmaxf(m_run[i], mt[i]);
            const float al = ex2((m_run[i] - m_new) * LOG2E);
            const float e0 = ex2((s[i].x - m_new) * LOG2E), e1 = ex2((s[i].y - m_new) * LOG2E);
            const float e2 = ex2((s[i].z - m_new) * LOG2E), e3 = ex2((s[i].w - m_new) * LOG2E);
            l_run[i] = l_run[i] * al + (e0 + e1) + (e2 + e3);
            m_run[i] = m_new;
            *(uint2*)(smem + OFF_AP + (k & 1) * 2560 + head * 80 + r * 8) = make_uint2(pack_bf16(e0, e1), pack_bf16(e2, e3));
            if (r == 0) ((float*)(smem + OFF_AALPHA))[(k & 1) * 32 + head] = al;
        }
        bar_arrive(BAR_P, 320);
    }
#pragma unroll
    for (int i = 0; i < 4; i++) {
        float l = l_run[i];
        l += __shfl_xor_sync(0xffffffffu, l, 1);
        l += __shfl_xor_sync(0xffffffffu, l, 2);
        l += __shfl_xor_sync(0xffffffffu, l, 4);
        if (r == 0) p.sc->ml[((16 * w + 4 * i + mat) * SPLIT + asp) * 4 + ab] = make_float2(m_run[i], l);
    }
    bar_arrive(BAR_E, 320);
}

__device__ __forceinline__ void attention_A(const Params& p, char* smem, int sw, int lane, int ab, int asp) {
    const uint32_t sbase = smem_u32(smem);
    const int tid = sw * 32 + lane;
    const int g = lane >> 2, t = lane & 3, mat = lane >> 3, r = lane & 7;
    const int mi = sw & 1, cq = sw >> 1;
    uint4 qf[8];
    {
        const unsigned* src = p.sc->qabs + ab * 8192 + sw * 1024 + lane * 4;
        for (int k = 0; k < TUNED(ASLEEP); k++) __nanosleep(1000);
        ll_poll4(qf, src, 128, 500);
        if (sw == 0) PROF(6);
    }
    bar_sync(BAR_S, NSW * 32);
    float oacc[2][8][4];
#pragma unroll
    for (int a = 0; a < 2; a++)
#pragma unroll
        for (int b = 0; b < 8; b++) zero4(oacc[a][b]);
    float* red = (float*)(smem + OFF_ARED) + (cq * 32 + 16 * mi + g) * 40 + 2 * t;
    const uint32_t qk_off = sbase + 2 * cq * 4096 + ((mat >> 1) * 8 + r) * 128 + (((mat & 1) ^ r) << 4);
    const uint32_t pv_off = sbase + sw * 4096 + ((mat & 1) * 8 + r) * 128 + (((mat >> 1) ^ r) << 4);
    const uint32_t p_off = sbase + OFF_AP + ((mat & 1) * 8 + r) * 80 + (mat >> 1) * 16;
    int st = 0, ph = 0, stp = 0;
    for (int k = -1; k < ATILES; k++) {
        float sacc[4][4];
        if (k + 1 < ATILES) {
            mbar_wait(sbase + OFF_BAR + (MB_AFULL + st) * 8, ph);
            if (k == -1 && sw == 0) PROF(13);
#pragma unroll
            for (int a = 0; a < 4; a++) zero4(sacc[a]);
#pragma unroll
            for (int ks = 0; ks < 8; ks++) {
#pragma unroll
                for (int np = 0; np < 2; np++) {
                    uint32_t b0, b1, b2, b3;
                    ldsm4(b0, b1, b2, b3, (qk_off ^ ((ks & 3) << 5)) + st * 32768 + (ks >> 2) * 4096 + np * 2048);
                    mma(sacc[2 * np], qf[ks].x, qf[ks].y, qf[ks].z, qf[ks].w, b0, b1);
                    mma(sacc[2 * np + 1], qf[ks].x, qf[ks].y, qf[ks].z, qf[ks].w, b2, b3);
                }
            }
        }
        if (k >= 0) bar_sync(BAR_P, 320);
        if (k + 1 < ATILES) {
#pragma unroll
            for (int nt = 0; nt < 4; nt++) {
                *(float2*)(red + 8 * nt) = make_float2(sacc[nt][0], sacc[nt][1]);
                *(float2*)(red + 8 * nt + 8 * 40) = make_float2(sacc[nt][2], sacc[nt][3]);
            }
            bar_arrive(BAR_R, 352);
        }
        if (k >= 0) {
            const float* alpha = (const float*)(smem + OFF_AALPHA) + (k & 1) * 32;
            const float al0 = alpha[g], al1 = alpha[g + 8], al2 = alpha[g + 16], al3 = alpha[g + 24];
            if (!__all_sync(0xffffffffu, al0 == 1.f && al1 == 1.f && al2 == 1.f && al3 == 1.f)) {
#pragma unroll
                for (int nt = 0; nt < 8; nt++) {
                    oacc[0][nt][0] *= al0; oacc[0][nt][1] *= al0; oacc[0][nt][2] *= al1; oacc[0][nt][3] *= al1;
                    oacc[1][nt][0] *= al2; oacc[1][nt][1] *= al2; oacc[1][nt][2] *= al3; oacc[1][nt][3] *= al3;
                }
            }
#pragma unroll
            for (int ks = 0; ks < 2; ks++) {
                uint32_t pa[2][4];
#pragma unroll
                for (int mt = 0; mt < 2; mt++)
                    ldsm4(pa[mt][0], pa[mt][1], pa[mt][2], pa[mt][3], p_off + (k & 1) * 2560 + mt * 16 * 80 + ks * 32);
#pragma unroll
                for (int np = 0; np < 4; np++) {
                    uint32_t b0, b1, b2, b3;
                    ldsm4t(b0, b1, b2, b3, (pv_off ^ (np << 5)) + stp * 32768 + ks * 2048);
#pragma unroll
                    for (int mt = 0; mt < 2; mt++) {
                        mma(oacc[mt][2 * np], pa[mt][0], pa[mt][1], pa[mt][2], pa[mt][3], b0, b1);
                        mma(oacc[mt][2 * np + 1], pa[mt][0], pa[mt][1], pa[mt][2], pa[mt][3], b2, b3);
                    }
                }
            }
        }
        stp = st;
        if (++st == ASTAGES) { st = 0; ph ^= 1; }
    }
    if (sw == 0) PROF(14);
    {
        float dep = 0.f;
#pragma unroll
        for (int nt = 0; nt < 8; nt++) dep += oacc[1][nt][0];
        warp_release(sbase + OFF_BAR + MB_F3 * 8, lane, dep);
    }
#pragma unroll
    for (int mt = 0; mt < 2; mt++)
#pragma unroll
        for (int hh = 0; hh < 2; hh++) {
            float4* op = (float4*)(p.sc->opart + ((16 * mt + 8 * hh + g) * SPLIT + asp) * 2048 + sw * 256 + ab * 64) + t;
#pragma unroll
            for (int q = 0; q < 4; q++)
                op[4 * q] = make_float4(oacc[mt][2 * q][2 * hh], oacc[mt][2 * q][2 * hh + 1],
                                    oacc[mt][2 * q + 1][2 * hh], oacc[mt][2 * q + 1][2 * hh + 1]);
        }
    bar_sync(BAR_E, 320);
    if (tid == 0) signal_counter(&p.sc->cnt);
    if (sw == 0) PROF(7);
}

__device__ __forceinline__ float matvec64(char* smem, const uint32_t (&xf)[4][2], int mb_full, int mb_free, int sw, int lane) {
    const uint32_t sbase = smem_u32(smem);
    const int g = lane >> 2, t = lane & 3, mat = lane >> 3, r = lane & 7;
    const uint32_t a = sbase + BLK_W + sw * 8192 + ((mat >> 1) * 8 + r) * 128 + (((mat & 1) ^ r) << 4);
    float c[4][4];
#pragma unroll
    for (int mt = 0; mt < 4; mt++) zero4(c[mt]);
    mbar_wait(sbase + OFF_BAR + (mb_full + (sw >> 1)) * 8, 0);
#pragma unroll
    for (int ks = 0; ks < 4; ks++)
#pragma unroll
        for (int mt = 0; mt < 4; mt++) {
            uint32_t a0, a1, a2, a3;
            ldsm4t(a0, a1, a2, a3, (a ^ (mt << 5)) + ks * 2048);
            mma(c[mt], a0, a1, a2, a3, xf[ks][0], xf[ks][1]);
        }
    warp_release(sbase + OFF_BAR + mb_free * 8, lane, (c[0][0] + c[1][0]) + (c[2][0] + c[3][0]));
    float* rp = (float*)(smem + OFF_RED);
#pragma unroll
    for (int mt = 0; mt < 4; mt++) {
        const float y0 = (t < 2 ? c[mt][0] : c[mt][2]) + __shfl_xor_sync(0xffffffffu, t < 2 ? c[mt][2] : c[mt][0], 2);
        const float y1 = (t < 2 ? c[mt][1] : c[mt][3]) + __shfl_xor_sync(0xffffffffu, t < 2 ? c[mt][3] : c[mt][1], 2);
        float* d = rp + sw * 256 + (t & 1) * 128 + 16 * mt + (t >> 1) * 8 + g;
        d[0] = y0;
        d[64] = y1;
    }
    bar_sync(BAR_S, NSW * 32);
    float y = 0.f;
#pragma unroll
    for (int i = 0; i < NSW; i++) y += rp[i * 256 + sw * 32 + lane];
    return y;
}
__device__ __forceinline__ void load_xfrags(const char* smem, uint32_t (&xf)[4][2], int sw, int lane) {
    const uint32_t* x32 = (const uint32_t*)(smem + OFF_X) + ((lane >> 2) & 3) * 256 + 32 * sw + (lane & 3);
#pragma unroll
    for (int ks = 0; ks < 4; ks++) {
        xf[ks][0] = lane < 16 ? x32[ks * 8] : 0u;
        xf[ks][1] = lane < 16 ? x32[ks * 8 + 4] : 0u;
    }
}
__device__ __forceinline__ int vec_word(int vid, int tid) { return (tid >> 6) * 2048 + (vid >> 1) * 32 + ((tid & 63) >> 1); }
__device__ __forceinline__ void store_vec(unsigned* dst, int vid, int tid, float y) {
    const float y1 = __shfl_down_sync(0xffffffffu, y, 1);
    if (!(tid & 1)) ll_store(dst + vec_word(vid, tid), pack_bf16(y, y1));
}
__device__ __forceinline__ void fill_qtab(const Params& p, char* smem, bool isA, int vid, int tid) {
    static_assert(R_LATE == 17, "rows");
    const int r = max(1 + (tid >> 4), isA ? R_JOIN : 0), pair = chunk_of(r, vid) >> 4;
    uint4 v[2];
    ll_poll4(v, p.sc->qB + pair * 64 + (tid & 15) * 4, (late_pair(vid) - pair) * 64, 300);
    *(uint4*)(smem + OFF_Q + 256 + tid * 16) = v[0];
    if (tid < 16) *(uint4*)(smem + OFF_Q + R_LATE * 256 + tid * 16) = v[1];
    __syncwarp();
    if ((tid & 31) == 0) mbar_expect_tx(smem_u32(smem) + OFF_BAR + MB_Q * 8, 0);
}
__device__ __forceinline__ void clear_handoffs(const Params& p, int vid, int tid) {
    const int chunk = chunk_of(R_LATE, vid);
    if (tid < 32) *(uint4*)(p.sc->part + chunk * 128 + tid * 4) = make_uint4(0, 0, 0, 0);
    if (tid == 32) *(uint2*)(p.sc->pml + chunk * 2) = make_uint2(0, 0);
    if ((tid >> 4) == 4 && vid < N_EARLY) *(uint4*)(p.sc->oB + vid * 64 + (tid & 15) * 4) = make_uint4(0, 0, 0, 0);
    if ((tid >> 2) == 24) *(uint4*)(p.out + vid * 32 + (tid & 3) * 8) = make_uint4(0, 0, 0, 0);
    if (!((vid | tid) & 1)) p.sc->ctx[vec_word(vid, tid)] = 0;
}
__device__ __forceinline__ void side_prologue(const Params& p, char* smem, bool isA, int vid, int sw, int lane) {
    const uint32_t sbase = smem_u32(smem);
    const uint32_t bars = sbase + OFF_BAR;
    const int h = vid & 31, j = vid >> 5;
    const int tid = sw * 32 + lane;
    const int g = lane >> 2, t = lane & 3, mat = lane >> 3, r = lane & 7;
    {
        uint32_t xf[4][2];
        mbar_wait(bars + MB_X * 8, 0);
        load_xfrags(smem, xf, sw, lane);
        if (sw == 0) PROF(16);
        store_vec((vid & 1) ? p.sc->qA : p.sc->qB, vid, tid, matvec64(smem, xf, MB_SIDE + SI_WQ, MB_F0, sw, lane));
        if (sw == 0) PROF(18);
    }
    if (tid == 255) asm volatile("fence.acq_rel.gpu;" ::: "memory");
    __syncwarp();
    __nanosleep(TUNED(GSLEEP));
    if (tid < 64) {
        uint4 v[1];
        ll_poll4(v, p.sc->qA + (tid >> 4) * 2048 + h * 64 + (tid & 15) * 4, 0, 300);
        *(uint4*)(smem + OFF_VEC + (tid >> 4) * 272 + (tid & 15) * 16) = v[0];
    }
    fill_qtab(p, smem, isA, vid, tid);
    bar_sync(BAR_S, NSW * 32);
    if (sw == 0) PROF(21);
    {
        mbar_wait(bars + (MB_SIDE + SI_WUK) * 8, 0);
        mbar_wait(bars + (MB_SIDE + SI_WUK + 1) * 8, 0);
        float c2[2][4];
        zero4(c2[0]); zero4(c2[1]);
        const uint32_t* qa = (const uint32_t*)(smem + OFF_VEC + (g & 3) * 272) + t;
        const uint32_t a = sbase + BLK_U + sw * 2048 + ((mat >> 1) * 8 + r) * 128 + (((mat & 1) ^ r) << 4);
#pragma unroll
        for (int ks = 0; ks < 8; ks++) {
            uint32_t b0, b1, b2, b3;
            ldsm4(b0, b1, b2, b3, (a ^ ((ks & 3) << 5)) + (ks >> 2) * 16384);
            const uint32_t a0 = qa[ks * 8], a2 = qa[ks * 8 + 4];
            mma(c2[0], a0, 0, a2, 0, b0, b1);
            mma(c2[1], a0, 0, a2, 0, b2, b3);
        }
        warp_release(bars + MB_FU * 8, lane, c2[0][0] + c2[1][0]);
        ll_store(p.sc->qabs + qabs_word(g & 3, h, j, sw, g >> 2, t),
                 g < 4 ? pack_bf16(c2[0][0], c2[0][1]) : pack_bf16(c2[1][0], c2[1][1]));
    }
    if (sw == 0) PROF(5);
}

__device__ __forceinline__ void side_epilogue(const Params& p, char* smem, bool isA, int vid, int sw, int lane) {
    const uint32_t sbase = smem_u32(smem);
    const uint32_t bars = sbase + OFF_BAR;
    const int tid = sw * 32 + lane;
    const int g = lane >> 2, t = lane & 3;
    mbar_wait(bars + MB_CNT * 8, 0);
    if (sw == 0) PROF(8);
    if (!(vid & 1)) {
        uint32_t of[4][2];
        const int h = vid >> 2;
        const int b = g & 3, sp = g >> 2;
        float wgt[SPLIT / 2];
        {
            float2 ml[SPLIT / 2];
            float M = -INFINITY, L = 0.f;
#pragma unroll
            for (int q = 0; q < SPLIT / 2; q++) { ml[q] = __ldcg(&p.sc->ml[(h * SPLIT + sp + 2 * q) * 4 + b]); M = fmaxf(M, ml[q].x); }
            M = fmaxf(M, __shfl_xor_sync(0xffffffffu, M, 16));
#pragma unroll
            for (int q = 0; q < SPLIT / 2; q++) { wgt[q] = ex2((ml[q].x - M) * LOG2E); L = fmaf(wgt[q], ml[q].y, L); }
            L += __shfl_xor_sync(0xffffffffu, L, 16);
#pragma unroll
            for (int q = 0; q < SPLIT / 2; q++) { wgt[q] /= L; mbar_wait(bars + (MB_SIDE + SI_OPART + q) * 8, 0); }
        }
#pragma unroll
        for (int ks = 0; ks < 4; ks++) {
            float v[4] = {0.f, 0.f, 0.f, 0.f};
#pragma unroll
            for (int q = 0; q < SPLIT / 2; q++) {
                const float4 u = *((const float4*)(smem + BLK_U) + (sp + 2 * q) * 512 + sw * 64 + b * 16 + 4 * ks + t);
                v[0] = fmaf(u.x, wgt[q], v[0]); v[1] = fmaf(u.y, wgt[q], v[1]);
                v[2] = fmaf(u.z, wgt[q], v[2]); v[3] = fmaf(u.w, wgt[q], v[3]);
            }
#pragma unroll
            for (int e = 0; e < 4; e++) v[e] += __shfl_xor_sync(0xffffffffu, v[e], 16);
#pragma unroll
            for (int hh = 0; hh < 2; hh++) {
                const uint32_t hi = pack_bf16(v[2 * hh], v[2 * hh + 1]);
                of[ks][hh] = sp == 0 ? hi : pack_bf16(v[2 * hh] - bf_lo(hi), v[2 * hh + 1] - bf_hi(hi));
            }
        }
        store_vec(p.sc->ctx, vid, tid, matvec64(smem, of, MB_SIDE + SI_WE, MB_F2, sw, lane));
        if (sw == 0) PROF(9);
    }
    const bool isB = !(vid & 1), late = isB && tid >= 240;
    const unsigned* xs = (isB ? p.sc->oB : p.sc->ctx) + (tid >> 4) * 512 + (vid >> 4) * 64 + (tid & 15) * 4;
    const uint32_t xa = sbase + OFF_X + t * (4 * XROW) + (lane & 8) * 4 + (lane & 16);
    const uint32_t wa = sbase + BLK_W + lane * 128 + ((sw ^ (lane & 7)) << 4);
    const int il = I_LAST - (isA ? 8 * R_JOIN : 0), sl = il % NS;
    const uint32_t va = sbase + OFF_RING + sl * TILE_BYTES + (sw >> 2) * 8192 + ((lane >> 4) * 8 + (lane & 7)) * 128 + (((2 * (sw & 3) + (g >> 1 & 1)) ^ (lane & 7)) << 4);
    uint32_t* out = (uint32_t*)(p.out + (g & 3) * 1024 + (isB ? 512 : 0) + ((vid >> 1) & 7) * 64 + 8 * sw) + t;
    unsigned* lp = p.sc->part + late_pair(vid) * 2048 + 16 * sw;
    unsigned* lm = p.sc->pml + late_pair(vid) * 32;
    const uint4* lf = (const uint4*)(smem + OFF_X + 4 * (3 * XROW + 192)) + t;
    __nv_bfloat16* lx = (__nv_bfloat16*)(smem + OFF_X) + 2 * (3 * XROW + 192) + 32 * (sw >> 1) + 16 * (t & 1) + ((lane & 16) >> 1) +
                        2 * (t & 2) + 2 * (sw & 1) + ((lane >> 3) & 1);
#pragma unroll 1
    for (int pass = 0; pass < 2; pass++) {
        const uint32_t wo = bars + (pass ? MB_SIDE + SI_WO : MB_X) * 8, vf = bars + (pass ? MB_FULL + sl : MB_X) * 8;
        uint4 v = make_uint4(1, 1, 1, 1), u0 = v, u1 = v;
        uint2 m0 = make_uint2(1, 1), m1 = m0;
        {
            mbar_wait(bars + (pass ? MB_PH : MB_CNT) * 8, 0);
            const float4 ma = *(const float4*)(smem + OFF_MLO), mb = *(const float4*)(smem + OFF_MLO + 16);
            const float M = fmaxf(fmaxf(ma.x, ma.z), fmaxf(mb.x, mb.z));
            const float a[4] = {ex2((ma.x - M) * LOG2E), ex2((ma.z - M) * LOG2E), ex2((mb.x - M) * LOG2E), ex2((mb.z - M) * LOG2E)};
            if (pass && tid == 0)
                ll_store2(lm + 2 * (vid & 15), __float_as_uint(M), __float_as_uint((a[0] * ma.y + a[1] * ma.w) + (a[2] * mb.y + a[3] * mb.w)));
            const int done = lds_volatile(sbase + OFF_DONE);
            float f = 0.f;
#pragma unroll
            for (int u = 0; u < 4; u++) {
                const uint4 p0 = *(const uint4*)(smem + OFF_PH + u * 128 + t * 32), p1 = *(const uint4*)(smem + OFF_PH + u * 128 + t * 32 + 16);
                const uint32_t pb[4][2] = {{p0.x, p0.y}, {p0.z, p0.w}, {p1.x, p1.y}, {p1.z, p1.w}};
                float c[4][4];
                mbar_wait(vf + u * 8, pass & (il / NS));
                if (sw == 0) PROF(u < 2 ? 19 + u : u);
#pragma unroll
                for (int k = 0; k < 4; k++) {
                    uint32_t a0, a1, a2, a3;
                    ldsm4t(a0, a1, a2, a3, va + u * TILE_BYTES + k * 2048);
                    zero4(c[k]);
                    mma(c[k], a0, a1, a2, a3, pb[k][0], pb[k][1]);
                }
                const float f0 = (c[0][0] + c[1][0]) + (c[2][0] + c[3][0]), f1 = (c[0][2] + c[1][2]) + (c[2][2] + c[3][2]);
                f = fmaf(a[u], (t & 1) ? f1 : f0, f);
                if (u == 3 && pass && t < 2) ll_store(lp + (vid & 15) * 128 + 8 * t + g, __float_as_uint(f));
                if (pass && tid == 0) sts_volatile(sbase + OFF_DONE, done + u + 1);
                if (u == TUNED(GO) && pass) {
                    if (!late) v = ll_load4(xs);
                    if (isB) { m0 = ll_load2(lm + 2 * g); m1 = ll_load2(lm + 2 * g + 16); }
                }
            }
            if (sw == 0) PROF(10);
        }
        for (unsigned spins = 0; !(ll_ok4(v) && ll_ok4(make_uint4(m0.x, m0.y, m1.x, m1.y))); spins++) {
            __nanosleep(200);
            if (!late) v = ll_load4(xs);
            if (isB) { m0 = ll_load2(lm + 2 * g); m1 = ll_load2(lm + 2 * g + 16); }
            if (spins > SPIN_LIMIT) __trap();
        }
        __syncwarp();
        if (!late) *(uint4*)(smem + OFF_X + (tid >> 6) * (4 * XROW) + (tid & 63) * 16) = make_uint4(~v.x, ~v.y, ~v.z, ~v.w);
        bar_sync(BAR_S, NSW * 32);
        if (sw == 0) PROF(15);
        float w0, w1;
        {
            const float a0 = __uint_as_float(~m0.x), a1 = __uint_as_float(~m1.x), M = redux_max(fmaxf(a0, a1));
            w0 = ex2((a0 - M) * LOG2E), w1 = ex2((a1 - M) * LOG2E);
            float l = w0 * __uint_as_float(~m0.y) + w1 * __uint_as_float(~m1.y);
#pragma unroll
            for (int k = 4; k < 32; k <<= 1) l += __shfl_xor_sync(0xffffffffu, l, k);
            w0 = __fdividef(w0, l), w1 = __fdividef(w1, l);
            if (pass && sw == 0 && !(vid & 15)) *(uint2*)(p.sc->qB + late_pair(vid) * 64 + 2 * lane) = make_uint2(0, 0);
        }
        float acc[4][4];
#pragma unroll
        for (int k = 0; k < 4; k++) zero4(acc[k]);
        uint32_t xf[4][4][4], b[4][4];
        auto rows = [&](int q) {
#pragma unroll
            for (int k = 0; k < 4; k++) ldsm4(xf[q][k][0], xf[q][k][1], xf[q][k][2], xf[q][k][3], xa + q * 256 + k * 64);
        };
        auto load = [&](int q, int h) {
#pragma unroll
            for (int k = 2 * h; k < 2 * h + 2; k++) ldsm4t(b[k][0], b[k][1], b[k][2], b[k][3], wa + q * TILE_BYTES + k * 4096);
        };
        auto mult = [&](int q) {
#pragma unroll
            for (int k = 0; k < 8; k++)
                mma(acc[k & 3], xf[q][k >> 1][0], xf[q][k >> 1][1], xf[q][k >> 1][2], xf[q][k >> 1][3], b[k >> 1][2 * (k & 1)], b[k >> 1][2 * (k & 1) + 1]);
        };
        rows(0); rows(1); rows(2); rows(3);
        mbar_wait(wo, 0);
        load(0, 0); load(0, 1); mult(0);
        if (isB) {
            const int z = lds_volatile(sbase + OFF_WIN + 4) + tiles4(TUNED(TRIG)) * TUNED(TAU) / 512;
            for (int k = pass ? 0 : 63; k < 64 && !__any_sync(0xffffffffu, (int)(now_ns() - z) >= 0); k++) __nanosleep(20);
            if (sw == 0) PROF(27);
            if (pass) { u0 = ll_load4(lp + g * 128 + 4 * t); u1 = ll_load4(lp + g * 128 + 4 * t + 1024); }
        }
        mbar_wait(wo + 8, 0);
        load(1, 0); load(1, 1); mult(1);
        if (isB) {
            for (unsigned spins = 0; !__all_sync(0xffffffffu, ll_ok4(u0) && ll_ok4(u1)); spins++) {
                if (sw == 0 && spins < 3) PROF2(150 + spins);
                u0 = ll_load4(lp + g * 128 + 4 * t); u1 = ll_load4(lp + g * 128 + 4 * t + 1024);
                if (spins > SPIN_LIMIT) __trap();
            }
            if (sw == 0) PROF2(153);
            const float o0 = w0 * __uint_as_float(~u0.x) + w1 * __uint_as_float(~u1.x), o1 = w0 * __uint_as_float(~u0.y) + w1 * __uint_as_float(~u1.y);
            const float o2 = w0 * __uint_as_float(~u0.z) + w1 * __uint_as_float(~u1.z), o3 = w0 * __uint_as_float(~u0.w) + w1 * __uint_as_float(~u1.w);
            const bool hi = lane & 16, mid = lane & 8;
            const float e0 = (hi ? o2 : o0) + __shfl_xor_sync(0xffffffffu, hi ? o0 : o2, 16);
            const float e1 = (hi ? o3 : o1) + __shfl_xor_sync(0xffffffffu, hi ? o1 : o3, 16);
            const float e = (mid ? e1 : e0) + __shfl_xor_sync(0xffffffffu, mid ? e0 : e1, 8);
            *lx = __float2bfloat16_rn(e + __shfl_xor_sync(0xffffffffu, e, 4));
            if (sw == 0) PROF(4);
        }
        bool r2 = mbar_test(wo + 16, 0);
        if (isB) bar_sync(BAR_S, NSW * 32);
        if (isB && g == 3) {
#pragma unroll
            for (int k = 0; k < 4; k++) {
                const uint4 f = lf[4 * k];
                xf[3][k][0] = f.x; xf[3][k][1] = f.y; xf[3][k][2] = f.z; xf[3][k][3] = f.w;
            }
        }
        mbar_wait_unless(r2, wo + 16);
        bool r3 = mbar_test(wo + 24, 0);
        load(2, 0); load(2, 1); mult(2);
        mbar_wait_unless(r3, wo + 24);
        r3 = mbar_try(wo + 32, 0);
        load(3, 0);
        mbar_wait_unless(r3, wo + 32);
        if (sw == 0) PROF(11);
        load(3, 1); mult(3);
        const uint32_t y = pack_bf16((acc[0][0] + acc[1][2]) + (acc[2][0] + acc[3][2]), (acc[0][1] + acc[1][3]) + (acc[2][1] + acc[3][3]));
        asm volatile("{\n .reg .pred q;\n setp.ne.u32 q, %2, 0;\n @q red.relaxed.gpu.global.add.noftz.bf16x2 [%0], %1;\n}"
                     ::"l"(out), "r"(y), "r"((int)(pass && lane < 16)) : "memory");
    }
    if (sw == 7) PROF(25);
    if (sw == 2) PROF(24);
}

__global__ void __launch_bounds__(NTHREADS, 1) fused_decode_kernel(const Ptrs ptrs, const __grid_constant__ Maps maps) {
    extern __shared__ __align__(1024) char smem[];
    Params p;
    static_cast<Ptrs&>(p) = ptrs;
    p.tm = maps.tm;
    const unsigned blk = blockIdx.x;
    asm volatile("{\n .reg .u64 a;\n .reg .u32 lo, hi;\n mov.b64 {lo, hi}, %0;\n mad.lo.u32 lo, %1, %3, lo;\n mad.lo.u32 lo, %2, 32, lo;\n"
                 " mov.b64 a, {lo, hi};\n prefetch.global.L2 [a];\n}" ::"l"(p.K), "r"(blk), "r"(threadIdx.x), "n"(NTHREADS * 32) : "memory");
    if (threadIdx.x == 0) first_load(p, smem_u32(smem), blk);
    const int warp = __shfl_sync(0xffffffffu, threadIdx.x >> 5, 0), lane = threadIdx.x & 31;
    const bool isA = blk % APER == APER - 1;
    const int aidx = blk / APER, ab = aidx / SPLIT, asp = aidx % SPLIT;
    const int vid = blk % APER * 16 + aidx;
    if (threadIdx.x == 32) next_loads(p, smem_u32(smem), vid);
    if (lane == 0 && warp != 1) {
        const int wu = max(warp, 1);
#pragma unroll
        for (int k = 0; k < (MB_COUNT - MB_EARLY + 10) / 11; k++) {
            const int i = MB_EARLY + k * 11 + wu - 1;
            if (i < MB_COUNT && i != MB_FULL) mbar_init(smem_u32(smem) + OFF_BAR + i * 8, i >= MB_F0 ? NSW : i == MB_PH ? 4 : 1);
        }
        fence_mbar_init();
        if (wu >= 2 && wu < 8) asm volatile("prefetch.tensormap [%0];" ::"l"(&p.tm[wu]) : "memory");
    }
    __syncwarp();
    if (threadIdx.x == 33) {
        *(int2*)(smem + OFF_DONE) = make_int2(0, 0);
        *(int2*)(smem + OFF_WIN) = make_int2(TUNED(WSTART), 0);
    }
    if (warp >= 4) clear_handoffs(p, vid, threadIdx.x - 128);
    bar_sync(0, NTHREADS);
    if (warp == 0) {
        produce(p, smem, lane, isA, vid, ab * 4096 + asp * 32);
    } else if (warp < 3) {
        if (isA) softmax_A(p, smem, warp - 1, lane, ab, asp);
        consume(p, smem, isA, vid, warp - 1, lane);
    } else if (warp == 3) {
        service(p, smem, isA, vid, lane);
    } else {
        const int sw = warp - 4;
        side_prologue(p, smem, isA, vid, sw, lane);
        if (isA) attention_A(p, smem, sw, lane, ab, asp);
        side_epilogue(p, smem, isA, vid, sw, lane);
    }
}

__device__ float g_tmp[2][4 * 32 * 512];
__device__ __forceinline__ float bfr(float x) { return __bfloat162float(__float2bfloat16_rn(x)); }
template <typename X>
__global__ void fb_matvec(const X* x, int xb, int xh, int K, const __nv_bfloat16* W, int wk, int wh, int wn, float* y,
                          __nv_bfloat16* out, bool round) {
    const int n = threadIdx.x, h = blockIdx.x, b = blockIdx.y;
    float s = 0.f;
    for (int k = 0; k < K; k++) s += (float)x[b * xb + h * xh + k] * __bfloat162float(W[(size_t)k * wk + h * wh + (size_t)n * wn]);
    if (out) out[b * 1024 + n] = __float2bfloat16_rn(s);
    else y[(b * gridDim.x + h) * blockDim.x + n] = round ? bfr(s) : s;
}
__global__ void fb_attn(const float* q, const __nv_bfloat16* K, const __nv_bfloat16* V, int D, size_t sb, size_t sh, float* o, bool round) {
    __shared__ float sc[4096], red[8];
    const int h = blockIdx.x, b = blockIdx.y, tid = threadIdx.x;
    K += b * sb + h * sh; V += b * sb + h * sh; q += (b * 32 + h) * D;
    float m = -INFINITY, l = 0.f;
    for (int k = tid; k < 4096; k += 256) {
        float s = 0.f;
        for (int d = 0; d < D; d++) s += q[d] * __bfloat162float(K[(size_t)k * D + d]);
        m = fmaxf(m, sc[k] = bfr(bfr(s) * SCALE));
    }
    m = warp_max(m);
    if (!(tid & 31)) red[tid >> 5] = m;
    __syncthreads();
    for (int i = 0; i < 8; i++) m = fmaxf(m, red[i]);
    __syncthreads();
    for (int k = tid; k < 4096; k += 256) { const float e = expf(sc[k] - m); l += e; sc[k] = bfr(e); }
    l = warp_sum(l);
    if (!(tid & 31)) red[tid >> 5] = l;
    __syncthreads();
    l = 0.f;
    for (int i = 0; i < 8; i++) l += red[i];
    for (int d = tid; d < D; d += 256) {
        float s = 0.f;
        for (int k = 0; k < 4096; k++) s += sc[k] * __bfloat162float(V[(size_t)k * D + d]);
        o[(b * 32 + h) * D + d] = round ? bfr(s / l) : s / l;
    }
}
void launch_fallback(void* const* d_in, __nv_bfloat16* out) {
    typedef const __nv_bfloat16* BP;
    float* t0;
    cudaGetSymbolAddress((void**)&t0, g_tmp);
    float* t1 = t0 + 4 * 32 * 512;
    const dim3 gh(32, 4), g1(1, 4);
    fb_matvec<<<gh, 128>>>((BP)d_in[0], 512, 0, 512, (BP)d_in[2], 4096, 128, 1, t0, nullptr, true);
    fb_matvec<<<gh, 512>>>((const float*)t0, 4096, 128, 128, (BP)d_in[3], 1, 128, 4096, t1, nullptr, true);
    fb_attn<<<gh, 256>>>(t1, (BP)d_in[1], (BP)d_in[1], 512, (size_t)4096 * 512, 0, t0, false);
    fb_matvec<<<gh, 128>>>((const float*)t0, 32 * 512, 512, 512, (BP)d_in[4], 4096, 128, 1, t1, nullptr, true);
    fb_matvec<<<g1, 512>>>((const float*)t1, 4096, 0, 4096, (BP)d_in[5], 512, 0, 1, nullptr, out, false);
    fb_matvec<<<gh, 128>>>((BP)d_in[6], 512, 0, 512, (BP)d_in[9], 4096, 128, 1, t0, nullptr, true);
    fb_attn<<<gh, 256>>>(t0, (BP)d_in[7], (BP)d_in[8], 128, (size_t)32 * 4096 * 128, (size_t)4096 * 128, t1, true);
    fb_matvec<<<g1, 512>>>((const float*)t1, 4096, 0, 4096, (BP)d_in[10], 512, 0, 1, nullptr, out + 512, false);
}

typedef CUresult (*EncodeFn)(CUtensorMap*, CUtensorMapDataType, cuuint32_t, void*, const cuuint64_t*, const cuuint64_t*,
                             const cuuint32_t*, const cuuint32_t*, CUtensorMapInterleave, CUtensorMapSwizzle,
                             CUtensorMapL2promotion, CUtensorMapFloatOOBfill);

void make_map(EncodeFn enc, CUtensorMap* tm, void* ptr, uint64_t cols, uint64_t rows, uint32_t br) {
    const cuuint64_t dims[2] = {cols, rows};
    const cuuint64_t strides[1] = {cols * 2};
    const cuuint32_t box[2] = {64, br};
    const cuuint32_t es[2] = {1, 1};
    enc(tm, CU_TENSOR_MAP_DATA_TYPE_BFLOAT16, 2, ptr, dims, strides, box, es, CU_TENSOR_MAP_INTERLEAVE_NONE,
        CU_TENSOR_MAP_SWIZZLE_128B, CU_TENSOR_MAP_L2_PROMOTION_NONE,
        CU_TENSOR_MAP_FLOAT_OOB_FILL_NONE);
}

}

extern "C" void kernel_launch(void* const* d_in, const int* in_sizes, int n_in, void* d_out, int out_size) {
    (void)in_sizes; (void)n_in; (void)out_size;
    void* fn = nullptr;
    cudaDriverEntryPointQueryResult qr;
    cudaGetDriverEntryPoint("cuTensorMapEncodeTiled", &fn, cudaEnableDefault, &qr);
    EncodeFn enc = (EncodeFn)fn;
    int dev = 0, sms = 0, per_sm = 0;
    cudaGetDevice(&dev);
    cudaDeviceGetAttribute(&sms, cudaDevAttrMultiProcessorCount, dev);
    cudaFuncSetAttribute(fused_decode_kernel, cudaFuncAttributeMaxDynamicSharedMemorySize, SMEM_BYTES);
    cudaOccupancyMaxActiveBlocksPerMultiprocessor(&per_sm, fused_decode_kernel, NTHREADS, SMEM_BYTES);
    if (!enc || sms * per_sm < NCTA || (uint32_t)(uintptr_t)d_in[7] > 0u - NCTA * NTHREADS * 32) {
        launch_fallback(d_in, (__nv_bfloat16*)d_out);
        return;
    }
    Ptrs p;
    Maps m;
    make_map(enc, &m.tm[0], d_in[9], 4096, 512, 128);
    make_map(enc, &m.tm[1], d_in[2], 4096, 512, 128);
    make_map(enc, &m.tm[2], d_in[10], 512, 4096, 64);
    make_map(enc, &m.tm[3], d_in[5], 512, 4096, 64);
    make_map(enc, &m.tm[4], d_in[3], 4096, 512, 128);
    make_map(enc, &m.tm[5], d_in[4], 4096, 512, 128);
    make_map(enc, &m.tm[6], d_in[1], 512, 4 * 4096, 32);
    make_map(enc, &m.tm[7], d_in[8], 128, 128 * 4096, TK);
    p.xA = (const __nv_bfloat16*)d_in[0];
    p.xB = (const __nv_bfloat16*)d_in[6];
    p.K = (const __nv_bfloat16*)d_in[7];
    p.V = (const __nv_bfloat16*)d_in[8];
    p.out = (__nv_bfloat16*)d_out;
    cudaGetSymbolAddress((void**)&p.sc, g_scratch);
    fused_decode_kernel<<<NCTA, NTHREADS, SMEM_BYTES>>>(p, m);
}
```
